```python
import torch

def _softmax(x, axis=-1):
    return torch.softmax(x, dim=axis)

def _gelu(x):
    return torch.nn.functional.gelu(x, approximate='tanh')

def _silu(x):
    return torch.nn.functional.silu(x)

def _sigmoid(x):
    return torch.sigmoid(x)

def _layernorm(x, axis=-1, eps=1e-05):
    m = x.mean(dim=axis, keepdim=True)
    v = x.var(dim=axis, keepdim=True, unbiased=False)
    return (x - m) / torch.sqrt(v + eps)

def _scatter_add(tgt, idx, src, axis=0):
    return tgt.clone().index_add_(axis, idx, src)

def _segment_sum(src, seg, n):
    out = torch.zeros((n,) + src.shape[1:], dtype=src.dtype)
    return out.index_add_(0, seg, src)

def _pad(x, pw):
    flat = tuple((v for pair in reversed(pw) for v in pair))
    return torch.nn.functional.pad(x, flat)
kernel_name = 'adaLN_cond__sliding_block__mixer_gmlp__prompt'

def setup_inputs():

    _w = lambda a: (lambda t: t.to(torch.bfloat16) if t.is_floating_point() else t)(torch.as_tensor(a))

    def _A_setup():
        B, S, D = (1, 2048, 448)
        return {'x': _w((lambda *s: torch.randn(*s, dtype=torch.bfloat16) * 0.05)(B, S, D)), 'wqkv': _w((lambda *s: torch.randn(*s, dtype=torch.bfloat16) * 0.05)(D, 3 * D)), 'wo': _w((lambda *s: torch.randn(*s, dtype=torch.bfloat16) * 0.05)(D, D))}
    _A_in = _A_setup()

    def _B_setup():
        B, S, D, F = (1, 2048, 448, 1792)
        Fh = F // 2
        return {'x': _w((lambda *s: torch.randn(*s, dtype=torch.bfloat16) * 0.05)(B, S, D)), 'w_in': _w((lambda *s: torch.randn(*s, dtype=torch.bfloat16) * 0.4)(D, 2 * Fh)), 'w_sp': _w(0.01 * (lambda *s: torch.randn(*s, dtype=torch.bfloat16) * 0.4)(S, S)), 'b_sp': _w(1.0 + 0.01 * (lambda *s: torch.randn(*s, dtype=torch.bfloat16) * 0.05)(S)), 'w_out': _w((lambda *s: torch.randn(*s, dtype=torch.bfloat16) * 0.05)(Fh, D))}
    _B_in = _B_setup()
    return {'A_x': _A_in['x'], 'A_wqkv': _A_in['wqkv'], 'A_wo': _A_in['wo'], 'B_x': _B_in['x'], 'B_w_in': _B_in['w_in'], 'B_w_sp': _B_in['w_sp'], 'B_b_sp': _B_in['b_sp'], 'B_w_out': _B_in['w_out'], 'c': _w((lambda *s: torch.randn(*s, dtype=torch.bfloat16) * 0.1)(1, 448) * 8.0), 'w_mod': _w((lambda *s: torch.randn(*s, dtype=torch.bfloat16) * 0.1)(448, 6 * 448) * 448 ** (-0.5) * 8.0)}

def reference(A_x, A_wqkv, A_wo, B_x, B_w_in, B_w_sp, B_b_sp, B_w_out, c, w_mod):

    def _A_ref(x, wqkv, wo):
        B, S, D = x.shape
        H = 16
        Dh = D // H
        W = 256
        qkv = (lambda x, *d: x.permute(*d))((x @ wqkv).reshape(B, S, 3, H, Dh), 2, 0, 3, 1, 4)
        q, k, v = (qkv[0], qkv[1], qkv[2])
        scores = torch.einsum('bhqd,bhkd->bhqk', q, k) * Dh ** (-0.5)
        idx = torch.arange(S)
        mask = (idx[:, None] - idx[None, :] >= 0) & (idx[:, None] - idx[None, :] < W)
        scores = torch.where(mask[None, None], scores, -1000000000.0)
        p = _softmax(scores, axis=-1)
        o = torch.einsum('bhqk,bhkd->bhqd', p, v)
        return (lambda x, *d: x.permute(*d))(o, 0, 2, 1, 3).reshape(B, S, D) @ wo

    def _B_ref(x, w_in, w_sp, b_sp, w_out):
        B, S, D = x.shape
        F = w_in.shape[-1]
        Fh = F // 2
        z = _gelu(torch.einsum('bsd,df->bsf', x, w_in))
        z1 = z[..., :Fh].clone()
        z2 = _layernorm(z[..., Fh:], axis=-1)
        g = torch.einsum('ts,bsf->btf', w_sp, z2) + b_sp[None, :, None]
        return torch.einsum('bsf,fd->bsd', z1 * g, w_out)
    x = A_x
    mod = (_silu(c) @ w_mod).reshape(c.shape[0], 6, 1, -1)
    sa, ca, ga, sb, cb, gb = (mod[:, 0].clone(), mod[:, 1].clone(), mod[:, 2].clone(), mod[:, 3].clone(), mod[:, 4].clone(), mod[:, 5].clone())
    h = _layernorm(x, axis=-1) * (1 + ca) + sa
    x = x + ga * _A_ref(h, A_wqkv, A_wo)
    h = _layernorm(x, axis=-1) * (1 + cb) + sb
    x = x + gb * _B_ref(h, B_w_in, B_w_sp, B_b_sp, B_w_out)
    return x
```

```cpp
#include <cuda_runtime.h>
#include <cuda_bf16.h>
#include <cuda.h>
#include <stdint.h>

namespace {

constexpr int SEQ = 2048, DM = 448, FH = 896;
constexpr uint32_t PG = 8192;
constexpr uint32_t MISC = 27 * PG;
constexpr uint32_t OFF_BAR = MISC + 2048;
constexpr uint32_t OFF_MOD1 = OFF_BAR + 1280;
constexpr uint32_t OFF_RED = OFF_MOD1 + 1792;
constexpr uint32_t OFF_MOD2 = OFF_RED + 256;
constexpr uint32_t OFF_GA = OFF_MOD2 + 1792;
constexpr uint32_t OFF_GB = OFF_GA + 448;
constexpr uint32_t OFF_ST1 = OFF_GB + 224;
constexpr uint32_t OFF_R5 = OFF_ST1 + 1024;
constexpr uint32_t OFF_ABORT = OFF_R5 + 2048;
constexpr uint32_t SMEM_BYTES = OFF_ABORT + 16;
constexpr uint32_t OFF_MU5 = 13 * PG + 4096;
constexpr uint32_t OFF_XB5_0 = 0;
constexpr uint32_t OFF_XB5_1 = 25 * PG + 4096;
static_assert(SMEM_BYTES <= 232448, "smem");

enum : int {
  B_X = 0, B_WK = B_X + 7, B_WV = B_WK + 7, B_WQ = B_WV + 7, B_KREM = B_WQ + 7, B_VREM,
  B_WO, B_A3 = B_WO + 7, B_Z2W = B_A3 + 7, B_Z1W = B_Z2W + 7, B_A4 = B_Z1W + 7  ,
  B_S5F = B_A4 + 14  , B_B6 = B_S5F + 16, B_A6 = B_B6 + 7  , B_XB5 = B_A6 + 14  , B_XB6 = B_XB5 + 2  ,
  B_TXEND = B_XB6 + 2,
  B_XFREE = B_TXEND, B_KPASS, B_VPASS, B_QPASS, B_ATT, B_S3MMA, B_A4RD  , B_Z2PASS = B_A4RD + 2,
  B_Z1C  , B_STG = B_Z1C + 3  , B_STGDONE = B_STG + 2, B_S5E  , B_X5FREE = B_S5E + 16, B_X6FREE,
  B_A6RD  , B_KRDY = B_A6RD + 4  , B_VRDY = B_KRDY + 2  , B_A4E = B_VRDY + 2, B_XRD, B_ST1  , B_MOD2 = B_ST1 + 2,
  B_COUNT
};
static_assert(B_COUNT * 8 <= 1280, "barriers");

constexpr int C_K = 0, C_V = 128, C_O = 256, C_X = 288, C_Z = 320, C_U = 352, C_COUNT = 416;

__device__ uint32_t g_epoch;
__device__ uint32_t g_mod[2688];
__device__ uint32_t g_cnt[C_COUNT * 8];
__device__ __align__(1024) uint8_t g_kv[16 * 8 * 2 * 16384];
__device__ __align__(1024) __nv_bfloat16 g_o[SEQ * DM];
__device__ __align__(1024) __nv_bfloat16 g_x1[SEQ * DM];
__device__ __align__(1024) __nv_bfloat16 g_u[SEQ * FH];
__device__ __align__(1024) uint8_t g_z2t[32 * FH * 128];
__device__ __align__(128) float2 g_st1[SEQ * 4];
__device__ __align__(128) float2 g_st2[SEQ * 8];
#define STAMP(i) do {} while (0)

struct Params {
  CUtensorMap x, wqkv, wo64, wo48, win64, win48, wsp, wout, o, x1, u;
  const __nv_bfloat16 *px, *pwo, *pwin, *pwsp, *pbsp, *pwout, *pc, *pwmod;
  __nv_bfloat16* out;
};

__device__ __forceinline__ uint32_t smem_u32(const void* p) { return (uint32_t)__cvta_generic_to_shared(p); }
__device__ __forceinline__ void mbar_init(uint32_t bar, uint32_t cnt) { asm volatile("mbarrier.init.shared::cta.b64 [%0], %1;" ::"r"(bar), "r"(cnt)); }
__device__ __forceinline__ void mbar_expect(uint32_t bar, uint32_t bytes) { asm volatile("mbarrier.arrive.expect_tx.shared::cta.b64 _, [%0], %1;" ::"r"(bar), "r"(bytes) : "memory"); }
__device__ __forceinline__ void mbar_arrive(uint32_t bar) { asm volatile("mbarrier.arrive.shared::cta.b64 _, [%0];" ::"r"(bar) : "memory"); }
__device__ __forceinline__ void mbar_arrive_remote(uint32_t rbar) { asm volatile("mbarrier.arrive.shared::cluster.b64 _, [%0];" ::"r"(rbar) : "memory"); }
__device__ __forceinline__ uint32_t mapa(uint32_t addr, uint32_t cta) { uint32_t r; asm volatile("mapa.shared::cluster.u32 %0, %1, %2;" : "=r"(r) : "r"(addr), "r"(cta)); return r; }
__device__ __forceinline__ void mbar_wait2(uint32_t bar, uint32_t ab) {
  asm volatile("{\n.reg .pred p;\n.reg .u32 n, f;\n"
               "mbarrier.try_wait.parity.shared::cta.b64 p, [%0], 0;\n@p bra WDONE;\nmov.u32 n, 0;\n"
               "WLOOP:\nmbarrier.try_wait.parity.shared::cta.b64 p, [%0], 0;\n@p bra WDONE;\n"
               "ld.volatile.shared.u32 f, [%1];\nadd.u32 n, n, 1;\nadd.u32 f, f, n;\nsetp.lt.u32 p, f, 0x40000;\n@p bra WLOOP;\n"
               "st.volatile.shared.u32 [%1], 0x40000;\nWDONE:\n}" ::"r"(bar), "r"(ab) : "memory");
}
__device__ __forceinline__ void warp_arrive(uint32_t bar, int lane) { __syncwarp(); if (lane == 0) mbar_arrive(bar); }
__device__ __forceinline__ void bar_sync(int id, int n) { asm volatile("bar.sync %0, %1;" ::"r"(id), "r"(n) : "memory"); }
__device__ __forceinline__ void bar_arrive(int id, int n) { asm volatile("bar.arrive %0, %1;" ::"r"(id), "r"(n) : "memory"); }
__device__ __forceinline__ void fence_async_smem() { asm volatile("fence.proxy.async.shared::cta;" ::: "memory"); }
__device__ __forceinline__ void fence_async_glob() { asm volatile("fence.proxy.async.global;" ::: "memory"); }
__device__ __forceinline__ void tma2d(uint32_t dst, const CUtensorMap* map, int c0, int c1, uint32_t bar) {
  asm volatile("cp.async.bulk.tensor.2d.shared::cluster.global.mbarrier::complete_tx::bytes [%0], [%1, {%3, %4}], [%2];"
               ::"r"(dst), "l"(map), "r"(bar), "r"(c0), "r"(c1) : "memory");
}
__device__ __forceinline__ void bulk_ld(uint32_t dst, const void* src, uint32_t bytes, uint32_t bar) {
  asm volatile("cp.async.bulk.shared::cluster.global.mbarrier::complete_tx::bytes [%0], [%1], %2, [%3];"
               ::"r"(dst), "l"(src), "r"(bytes), "r"(bar) : "memory");
}
__device__ __forceinline__ void bulk_st(void* dst, uint32_t src, uint32_t bytes) {
  asm volatile("cp.async.bulk.global.shared::cta.bulk_group [%0], [%1], %2;" ::"l"(dst), "r"(src), "r"(bytes) : "memory");
  asm volatile("cp.async.bulk.commit_group;" ::: "memory");
  asm volatile("cp.async.bulk.wait_group 0;" ::: "memory");
}
__device__ __forceinline__ void l2_prefetch(const void* p, uint32_t bytes) { asm volatile("cp.async.bulk.prefetch.L2.global [%0], %1;" ::"l"(p), "r"(bytes) : "memory"); }
__device__ __forceinline__ void prefetch_map(const CUtensorMap* m) { asm volatile("prefetch.tensormap [%0];" ::"l"(m) : "memory"); }
__device__ __forceinline__ uint32_t ld_acquire(const uint32_t* p) { uint32_t v; asm volatile("ld.acquire.gpu.global.u32 %0, [%1];" : "=r"(v) : "l"(p) : "memory"); return v; }
__device__ __forceinline__ uint32_t ld_relaxed(const uint32_t* p) { uint32_t v; asm volatile("ld.relaxed.gpu.global.u32 %0, [%1];" : "=r"(v) : "l"(p) : "memory"); return v; }
__device__ __forceinline__ uint4 ld_relaxed4(const uint32_t* p) {
  uint4 v; asm volatile("ld.relaxed.gpu.global.v4.u32 {%0,%1,%2,%3}, [%4];" : "=r"(v.x), "=r"(v.y), "=r"(v.z), "=r"(v.w) : "l"(p) : "memory"); return v;
}
__device__ __forceinline__ void st_relaxed(uint32_t* p, uint32_t v) { asm volatile("st.relaxed.gpu.global.u32 [%0], %1;" ::"l"(p), "r"(v) : "memory"); }
__device__ __forceinline__ void publish(int c) { asm volatile("red.release.gpu.global.add.u32 [%0], 1;" ::"l"(&g_cnt[c * 8]) : "memory"); }
__device__ __forceinline__ bool give_up(uint32_t& n, uint32_t ab) {
  uint32_t f; asm volatile("ld.volatile.shared.u32 %0, [%1];" : "=r"(f) : "r"(ab) : "memory");
  if (++n + f < 0x40000u) return false;
  asm volatile("st.volatile.shared.u32 [%0], 0x40000;" ::"r"(ab) : "memory");
  return true;
}
__device__ __forceinline__ void poll2(int c, uint32_t target, uint32_t ab) {
  uint32_t n = 0;
  while ((int)(ld_acquire(&g_cnt[c * 8]) - target) < 0) { if (give_up(n, ab)) break; }
}
__device__ __forceinline__ void ldsm4(uint32_t* r, uint32_t addr) {
  asm volatile("ldmatrix.sync.aligned.m8n8.x4.shared.b16 {%0,%1,%2,%3}, [%4];" : "=r"(r[0]), "=r"(r[1]), "=r"(r[2]), "=r"(r[3]) : "r"(addr) : "memory");
}
__device__ __forceinline__ void stsm4(uint32_t addr, uint32_t r0, uint32_t r1, uint32_t r2, uint32_t r3) {
  asm volatile("stmatrix.sync.aligned.m8n8.x4.shared.b16 [%0], {%1,%2,%3,%4};" ::"r"(addr), "r"(r0), "r"(r1), "r"(r2), "r"(r3) : "memory");
}
__device__ __forceinline__ void stsm4t(uint32_t addr, uint32_t r0, uint32_t r1, uint32_t r2, uint32_t r3) {
  asm volatile("stmatrix.sync.aligned.m8n8.x4.trans.shared.b16 [%0], {%1,%2,%3,%4};" ::"r"(addr), "r"(r0), "r"(r1), "r"(r2), "r"(r3) : "memory");
}
__device__ __forceinline__ uint4 lds128(uint32_t addr) {
  uint4 v; asm volatile("ld.shared.v4.u32 {%0,%1,%2,%3}, [%4];" : "=r"(v.x), "=r"(v.y), "=r"(v.z), "=r"(v.w) : "r"(addr) : "memory"); return v;
}
__device__ __forceinline__ float2 lds64f(uint32_t addr) {
  float2 v; asm volatile("ld.shared.v2.f32 {%0,%1}, [%2];" : "=f"(v.x), "=f"(v.y) : "r"(addr) : "memory"); return v;
}
__device__ __forceinline__ void sts16(uint32_t addr, uint32_t v) { asm volatile("st.shared.u16 [%0], %1;" ::"r"(addr), "h"((uint16_t)v) : "memory"); }
__device__ __forceinline__ void sts32(uint32_t addr, uint32_t v) { asm volatile("st.shared.u32 [%0], %1;" ::"r"(addr), "r"(v) : "memory"); }
__device__ __forceinline__ void sts32f(uint32_t addr, float v) { asm volatile("st.shared.f32 [%0], %1;" ::"r"(addr), "f"(v) : "memory"); }
__device__ __forceinline__ float lds32f(uint32_t addr) { float v; asm volatile("ld.shared.f32 %0, [%1];" : "=f"(v) : "r"(addr) : "memory"); return v; }
__device__ __forceinline__ void sts128(uint32_t addr, uint4 v) { asm volatile("st.shared.v4.u32 [%0], {%1,%2,%3,%4};" ::"r"(addr), "r"(v.x), "r"(v.y), "r"(v.z), "r"(v.w) : "memory"); }
__device__ __forceinline__ void st_async4(uint32_t raddr, uint32_t a, uint32_t b, uint32_t c, uint32_t d, uint32_t rbar) {
  asm volatile("st.async.shared::cluster.mbarrier::complete_tx::bytes.v4.b32 [%0], {%1,%2,%3,%4}, [%5];" ::"r"(raddr), "r"(a), "r"(b), "r"(c), "r"(d), "r"(rbar) : "memory");
}
__device__ __forceinline__ void st_async2(uint32_t raddr, uint32_t a, uint32_t b, uint32_t rbar) {
  asm volatile("st.async.shared::cluster.mbarrier::complete_tx::bytes.v2.b32 [%0], {%1,%2}, [%3];" ::"r"(raddr), "r"(a), "r"(b), "r"(rbar) : "memory");
}
__device__ __forceinline__ uint32_t pack2(float lo, float hi) { uint32_t r; asm("cvt.rn.bf16x2.f32 %0, %1, %2;" : "=r"(r) : "f"(hi), "f"(lo)); return r; }
__device__ __forceinline__ float bf_lo(uint32_t w) { return __uint_as_float(w << 16); }
__device__ __forceinline__ float bf_hi(uint32_t w) { return __uint_as_float(w & 0xFFFF0000u); }
__device__ __forceinline__ uint32_t hfma2(uint32_t a, uint32_t b, uint32_t c) { uint32_t r; asm("fma.rn.bf16x2 %0, %1, %2, %3;" : "=r"(r) : "r"(a), "r"(b), "r"(c)); return r; }
__device__ __forceinline__ uint32_t hmul2(uint32_t a, uint32_t b) { uint32_t r; asm("mul.rn.bf16x2 %0, %1, %2;" : "=r"(r) : "r"(a), "r"(b)); return r; }
__device__ __forceinline__ uint32_t hsub2(uint32_t a, uint32_t b) { uint32_t r; asm("sub.rn.bf16x2 %0, %1, %2;" : "=r"(r) : "r"(a), "r"(b)); return r; }
__device__ __forceinline__ float ex2(float x) { float r; asm("ex2.approx.ftz.f32 %0, %1;" : "=f"(r) : "f"(x)); return r; }
__device__ __forceinline__ float gelu(float x) {
  float u = x * fmaf(0.0356774081f, x * x, 0.7978845608f), t;
  asm("tanh.approx.f32 %0, %1;" : "=f"(t) : "f"(u));
  float hx = 0.5f * x;
  return fmaf(hx, t, hx);
}
__device__ __forceinline__ float quad_sum(float v) { v += __shfl_xor_sync(~0u, v, 1); v += __shfl_xor_sync(~0u, v, 2); return v; }
__device__ __forceinline__ float quad_max(float v) { v = fmaxf(v, __shfl_xor_sync(~0u, v, 1)); v = fmaxf(v, __shfl_xor_sync(~0u, v, 2)); return v; }
__device__ __forceinline__ void rowsum_mma(float* c, const uint32_t* a) {
  asm volatile("mma.sync.aligned.m16n8k16.row.col.f32.bf16.bf16.f32 {%0,%1,%2,%3}, {%4,%5,%6,%7}, {%8,%8}, {%0,%1,%2,%3};"
               : "+f"(c[0]), "+f"(c[1]), "+f"(c[2]), "+f"(c[3]) : "r"(a[0]), "r"(a[1]), "r"(a[2]), "r"(a[3]), "r"(0x3F803F80u));
}
__device__ __forceinline__ void wg_fence() { asm volatile("wgmma.fence.sync.aligned;" ::: "memory"); }
__device__ __forceinline__ void wg_commit() { asm volatile("wgmma.commit_group.sync.aligned;" ::: "memory"); }
template <int N> __device__ __forceinline__ void wg_wait() { asm volatile("wgmma.wait_group.sync.aligned %0;" ::"n"(N) : "memory"); }
__device__ __forceinline__ uint64_t mkdesc(uint32_t dbase, uint32_t off, uint32_t lbo) {
  return (uint64_t)(dbase + (off >> 4) + ((lbo >> 4) << 16)) | ((uint64_t)0x40000040u << 32);
}
template <int N> __device__ __forceinline__ void keep(float* d) {
#pragma unroll
  for (int i = 0; i < N; i++) asm volatile("" : "+f"(d[i]));
}

template <int TB> __device__ __forceinline__ void wg_rs32(float* d, const uint32_t* a, uint64_t db, int sd) {
  asm volatile("{\n.reg .pred p;\nsetp.ne.b32 p, %21, 0;\n"
    "wgmma.mma_async.sync.aligned.m64n32k16.f32.bf16.bf16 {%0, %1, %2, %3, %4, %5, %6, %7, %8, %9, %10, %11, %12, %13, %14, %15}, {%16, %17, %18, %19}, %20, p, 1, 1, %22;\n}"
    : "+f"(d[0]), "+f"(d[1]), "+f"(d[2]), "+f"(d[3]), "+f"(d[4]), "+f"(d[5]), "+f"(d[6]), "+f"(d[7]), "+f"(d[8]), "+f"(d[9]), "+f"(d[10]), "+f"(d[11]), "+f"(d[12]), "+f"(d[13]), "+f"(d[14]), "+f"(d[15])
    : "r"(a[0]), "r"(a[1]), "r"(a[2]), "r"(a[3]), "l"(db), "r"(sd), "n"(TB));
}
template <int TB> __device__ __forceinline__ void wg_rs56(float* d, const uint32_t* a, uint64_t db, int sd) {
  asm volatile("{\n.reg .pred p;\nsetp.ne.b32 p, %33, 0;\n"
    "wgmma.mma_async.sync.aligned.m64n56k16.f32.bf16.bf16 {%0, %1, %2, %3, %4, %5, %6, %7, %8, %9, %10, %11, %12, %13, %14, %15, %16, %17, %18, %19, %20, %21, %22, %23, %24, %25, %26, %27}, {%28, %29, %30, %31}, %32, p, 1, 1, %34;\n}"
    : "+f"(d[0]), "+f"(d[1]), "+f"(d[2]), "+f"(d[3]), "+f"(d[4]), "+f"(d[5]), "+f"(d[6]), "+f"(d[7]), "+f"(d[8]), "+f"(d[9]), "+f"(d[10]), "+f"(d[11]), "+f"(d[12]), "+f"(d[13]), "+f"(d[14]), "+f"(d[15]), "+f"(d[16]), "+f"(d[17]), "+f"(d[18]), "+f"(d[19]), "+f"(d[20]), "+f"(d[21]), "+f"(d[22]), "+f"(d[23]), "+f"(d[24]), "+f"(d[25]), "+f"(d[26]), "+f"(d[27])
    : "r"(a[0]), "r"(a[1]), "r"(a[2]), "r"(a[3]), "l"(db), "r"(sd), "n"(TB));
}
template <int TB> __device__ __forceinline__ void wg_rs64(float* d, const uint32_t* a, uint64_t db, int sd) {
  asm volatile("{\n.reg .pred p;\nsetp.ne.b32 p, %37, 0;\n"
    "wgmma.mma_async.sync.aligned.m64n64k16.f32.bf16.bf16 {%0, %1, %2, %3, %4, %5, %6, %7, %8, %9, %10, %11, %12, %13, %14, %15, %16, %17, %18, %19, %20, %21, %22, %23, %24, %25, %26, %27, %28, %29, %30, %31}, {%32, %33, %34, %35}, %36, p, 1, 1, %38;\n}"
    : "+f"(d[0]), "+f"(d[1]), "+f"(d[2]), "+f"(d[3]), "+f"(d[4]), "+f"(d[5]), "+f"(d[6]), "+f"(d[7]), "+f"(d[8]), "+f"(d[9]), "+f"(d[10]), "+f"(d[11]), "+f"(d[12]), "+f"(d[13]), "+f"(d[14]), "+f"(d[15]), "+f"(d[16]), "+f"(d[17]), "+f"(d[18]), "+f"(d[19]), "+f"(d[20]), "+f"(d[21]), "+f"(d[22]), "+f"(d[23]), "+f"(d[24]), "+f"(d[25]), "+f"(d[26]), "+f"(d[27]), "+f"(d[28]), "+f"(d[29]), "+f"(d[30]), "+f"(d[31])
    : "r"(a[0]), "r"(a[1]), "r"(a[2]), "r"(a[3]), "l"(db), "r"(sd), "n"(TB));
}
template <int TB> __device__ __forceinline__ void wg_rs112(float* d, const uint32_t* a, uint64_t db, int sd) {
  asm volatile("{\n.reg .pred p;\nsetp.ne.b32 p, %61, 0;\n"
    "wgmma.mma_async.sync.aligned.m64n112k16.f32.bf16.bf16 {%0, %1, %2, %3, %4, %5, %6, %7, %8, %9, %10, %11, %12, %13, %14, %15, %16, %17, %18, %19, %20, %21, %22, %23, %24, %25, %26, %27, %28, %29, %30, %31, %32, %33, %34, %35, %36, %37, %38, %39, %40, %41, %42, %43, %44, %45, %46, %47, %48, %49, %50, %51, %52, %53, %54, %55}, {%56, %57, %58, %59}, %60, p, 1, 1, %62;\n}"
    : "+f"(d[0]), "+f"(d[1]), "+f"(d[2]), "+f"(d[3]), "+f"(d[4]), "+f"(d[5]), "+f"(d[6]), "+f"(d[7]), "+f"(d[8]), "+f"(d[9]), "+f"(d[10]), "+f"(d[11]), "+f"(d[12]), "+f"(d[13]), "+f"(d[14]), "+f"(d[15]), "+f"(d[16]), "+f"(d[17]), "+f"(d[18]), "+f"(d[19]), "+f"(d[20]), "+f"(d[21]), "+f"(d[22]), "+f"(d[23]), "+f"(d[24]), "+f"(d[25]), "+f"(d[26]), "+f"(d[27]), "+f"(d[28]), "+f"(d[29]), "+f"(d[30]), "+f"(d[31]), "+f"(d[32]), "+f"(d[33]), "+f"(d[34]), "+f"(d[35]), "+f"(d[36]), "+f"(d[37]), "+f"(d[38]), "+f"(d[39]), "+f"(d[40]), "+f"(d[41]), "+f"(d[42]), "+f"(d[43]), "+f"(d[44]), "+f"(d[45]), "+f"(d[46]), "+f"(d[47]), "+f"(d[48]), "+f"(d[49]), "+f"(d[50]), "+f"(d[51]), "+f"(d[52]), "+f"(d[53]), "+f"(d[54]), "+f"(d[55])
    : "r"(a[0]), "r"(a[1]), "r"(a[2]), "r"(a[3]), "l"(db), "r"(sd), "n"(TB));
}
template <int TB> __device__ __forceinline__ void wg_rs192(float* d, const uint32_t* a, uint64_t db, int sd) {
  asm volatile("{\n.reg .pred p;\nsetp.ne.b32 p, %101, 0;\n"
    "wgmma.mma_async.sync.aligned.m64n192k16.f32.bf16.bf16 {%0, %1, %2, %3, %4, %5, %6, %7, %8, %9, %10, %11, %12, %13, %14, %15, %16, %17, %18, %19, %20, %21, %22, %23, %24, %25, %26, %27, %28, %29, %30, %31, %32, %33, %34, %35, %36, %37, %38, %39, %40, %41, %42, %43, %44, %45, %46, %47, %48, %49, %50, %51, %52, %53, %54, %55, %56, %57, %58, %59, %60, %61, %62, %63, %64, %65, %66, %67, %68, %69, %70, %71, %72, %73, %74, %75, %76, %77, %78, %79, %80, %81, %82, %83, %84, %85, %86, %87, %88, %89, %90, %91, %92, %93, %94, %95}, {%96, %97, %98, %99}, %100, p, 1, 1, %102;\n}"
    : "+f"(d[0]), "+f"(d[1]), "+f"(d[2]), "+f"(d[3]), "+f"(d[4]), "+f"(d[5]), "+f"(d[6]), "+f"(d[7]), "+f"(d[8]), "+f"(d[9]), "+f"(d[10]), "+f"(d[11]), "+f"(d[12]), "+f"(d[13]), "+f"(d[14]), "+f"(d[15]), "+f"(d[16]), "+f"(d[17]), "+f"(d[18]), "+f"(d[19]), "+f"(d[20]), "+f"(d[21]), "+f"(d[22]), "+f"(d[23]), "+f"(d[24]), "+f"(d[25]), "+f"(d[26]), "+f"(d[27]), "+f"(d[28]), "+f"(d[29]), "+f"(d[30]), "+f"(d[31]), "+f"(d[32]), "+f"(d[33]), "+f"(d[34]), "+f"(d[35]), "+f"(d[36]), "+f"(d[37]), "+f"(d[38]), "+f"(d[39]), "+f"(d[40]), "+f"(d[41]), "+f"(d[42]), "+f"(d[43]), "+f"(d[44]), "+f"(d[45]), "+f"(d[46]), "+f"(d[47]), "+f"(d[48]), "+f"(d[49]), "+f"(d[50]), "+f"(d[51]), "+f"(d[52]), "+f"(d[53]), "+f"(d[54]), "+f"(d[55]), "+f"(d[56]), "+f"(d[57]), "+f"(d[58]), "+f"(d[59]), "+f"(d[60]), "+f"(d[61]), "+f"(d[62]), "+f"(d[63]), "+f"(d[64]), "+f"(d[65]), "+f"(d[66]), "+f"(d[67]), "+f"(d[68]), "+f"(d[69]), "+f"(d[70]), "+f"(d[71]), "+f"(d[72]), "+f"(d[73]), "+f"(d[74]), "+f"(d[75]), "+f"(d[76]), "+f"(d[77]), "+f"(d[78]), "+f"(d[79]), "+f"(d[80]), "+f"(d[81]), "+f"(d[82]), "+f"(d[83]), "+f"(d[84]), "+f"(d[85]), "+f"(d[86]), "+f"(d[87]), "+f"(d[88]), "+f"(d[89]), "+f"(d[90]), "+f"(d[91]), "+f"(d[92]), "+f"(d[93]), "+f"(d[94]), "+f"(d[95])
    : "r"(a[0]), "r"(a[1]), "r"(a[2]), "r"(a[3]), "l"(db), "r"(sd), "n"(TB));
}
template <int TB> __device__ __forceinline__ void wg_rs224(float* d, const uint32_t* a, uint64_t db, int sd) {
  asm volatile("{\n.reg .pred p;\nsetp.ne.b32 p, %117, 0;\n"
    "wgmma.mma_async.sync.aligned.m64n224k16.f32.bf16.bf16 {%0, %1, %2, %3, %4, %5, %6, %7, %8, %9, %10, %11, %12, %13, %14, %15, %16, %17, %18, %19, %20, %21, %22, %23, %24, %25, %26, %27, %28, %29, %30, %31, %32, %33, %34, %35, %36, %37, %38, %39, %40, %41, %42, %43, %44, %45, %46, %47, %48, %49, %50, %51, %52, %53, %54, %55, %56, %57, %58, %59, %60, %61, %62, %63, %64, %65, %66, %67, %68, %69, %70, %71, %72, %73, %74, %75, %76, %77, %78, %79, %80, %81, %82, %83, %84, %85, %86, %87, %88, %89, %90, %91, %92, %93, %94, %95, %96, %97, %98, %99, %100, %101, %102, %103, %104, %105, %106, %107, %108, %109, %110, %111}, {%112, %113, %114, %115}, %116, p, 1, 1, %118;\n}"
    : "+f"(d[0]), "+f"(d[1]), "+f"(d[2]), "+f"(d[3]), "+f"(d[4]), "+f"(d[5]), "+f"(d[6]), "+f"(d[7]), "+f"(d[8]), "+f"(d[9]), "+f"(d[10]), "+f"(d[11]), "+f"(d[12]), "+f"(d[13]), "+f"(d[14]), "+f"(d[15]), "+f"(d[16]), "+f"(d[17]), "+f"(d[18]), "+f"(d[19]), "+f"(d[20]), "+f"(d[21]), "+f"(d[22]), "+f"(d[23]), "+f"(d[24]), "+f"(d[25]), "+f"(d[26]), "+f"(d[27]), "+f"(d[28]), "+f"(d[29]), "+f"(d[30]), "+f"(d[31]), "+f"(d[32]), "+f"(d[33]), "+f"(d[34]), "+f"(d[35]), "+f"(d[36]), "+f"(d[37]), "+f"(d[38]), "+f"(d[39]), "+f"(d[40]), "+f"(d[41]), "+f"(d[42]), "+f"(d[43]), "+f"(d[44]), "+f"(d[45]), "+f"(d[46]), "+f"(d[47]), "+f"(d[48]), "+f"(d[49]), "+f"(d[50]), "+f"(d[51]), "+f"(d[52]), "+f"(d[53]), "+f"(d[54]), "+f"(d[55]), "+f"(d[56]), "+f"(d[57]), "+f"(d[58]), "+f"(d[59]), "+f"(d[60]), "+f"(d[61]), "+f"(d[62]), "+f"(d[63]), "+f"(d[64]), "+f"(d[65]), "+f"(d[66]), "+f"(d[67]), "+f"(d[68]), "+f"(d[69]), "+f"(d[70]), "+f"(d[71]), "+f"(d[72]), "+f"(d[73]), "+f"(d[74]), "+f"(d[75]), "+f"(d[76]), "+f"(d[77]), "+f"(d[78]), "+f"(d[79]), "+f"(d[80]), "+f"(d[81]), "+f"(d[82]), "+f"(d[83]), "+f"(d[84]), "+f"(d[85]), "+f"(d[86]), "+f"(d[87]), "+f"(d[88]), "+f"(d[89]), "+f"(d[90]), "+f"(d[91]), "+f"(d[92]), "+f"(d[93]), "+f"(d[94]), "+f"(d[95]), "+f"(d[96]), "+f"(d[97]), "+f"(d[98]), "+f"(d[99]), "+f"(d[100]), "+f"(d[101]), "+f"(d[102]), "+f"(d[103]), "+f"(d[104]), "+f"(d[105]), "+f"(d[106]), "+f"(d[107]), "+f"(d[108]), "+f"(d[109]), "+f"(d[110]), "+f"(d[111])
    : "r"(a[0]), "r"(a[1]), "r"(a[2]), "r"(a[3]), "l"(db), "r"(sd), "n"(TB));
}
template <int TB> __device__ __forceinline__ void wg_ss112(float* d, uint64_t da, uint64_t db, int sd) {
  asm volatile("{\n.reg .pred p;\nsetp.ne.b32 p, %58, 0;\n"
    "wgmma.mma_async.sync.aligned.m64n112k16.f32.bf16.bf16 {%0, %1, %2, %3, %4, %5, %6, %7, %8, %9, %10, %11, %12, %13, %14, %15, %16, %17, %18, %19, %20, %21, %22, %23, %24, %25, %26, %27, %28, %29, %30, %31, %32, %33, %34, %35, %36, %37, %38, %39, %40, %41, %42, %43, %44, %45, %46, %47, %48, %49, %50, %51, %52, %53, %54, %55}, %56, %57, p, 1, 1, 0, %59;\n}"
    : "+f"(d[0]), "+f"(d[1]), "+f"(d[2]), "+f"(d[3]), "+f"(d[4]), "+f"(d[5]), "+f"(d[6]), "+f"(d[7]), "+f"(d[8]), "+f"(d[9]), "+f"(d[10]), "+f"(d[11]), "+f"(d[12]), "+f"(d[13]), "+f"(d[14]), "+f"(d[15]), "+f"(d[16]), "+f"(d[17]), "+f"(d[18]), "+f"(d[19]), "+f"(d[20]), "+f"(d[21]), "+f"(d[22]), "+f"(d[23]), "+f"(d[24]), "+f"(d[25]), "+f"(d[26]), "+f"(d[27]), "+f"(d[28]), "+f"(d[29]), "+f"(d[30]), "+f"(d[31]), "+f"(d[32]), "+f"(d[33]), "+f"(d[34]), "+f"(d[35]), "+f"(d[36]), "+f"(d[37]), "+f"(d[38]), "+f"(d[39]), "+f"(d[40]), "+f"(d[41]), "+f"(d[42]), "+f"(d[43]), "+f"(d[44]), "+f"(d[45]), "+f"(d[46]), "+f"(d[47]), "+f"(d[48]), "+f"(d[49]), "+f"(d[50]), "+f"(d[51]), "+f"(d[52]), "+f"(d[53]), "+f"(d[54]), "+f"(d[55])
    : "l"(da), "l"(db), "r"(sd), "n"(TB));
}

__device__ __forceinline__ int perm448(int k) { return (k >> 5) * 32 + ((k & 7) >> 1) * 8 + ((k >> 4) & 1) * 4 + ((k >> 3) & 1) * 2 + (k & 1); }
__device__ __forceinline__ int perm64(int k) { return ((k & 7) >> 1) * 16 + (k >> 4) * 4 + ((k >> 3) & 1) * 2 + (k & 1); }

__device__ __forceinline__ float silu_bf(float c) { return bf_lo(pack2(c / (1.f + __expf(-c)), 0.f)); }
__device__ __forceinline__ void fma8(float* acc, uint4 w, float s) {
  acc[0] = fmaf(bf_lo(w.x), s, acc[0]); acc[1] = fmaf(bf_hi(w.x), s, acc[1]);
  acc[2] = fmaf(bf_lo(w.y), s, acc[2]); acc[3] = fmaf(bf_hi(w.y), s, acc[3]);
  acc[4] = fmaf(bf_lo(w.z), s, acc[4]); acc[5] = fmaf(bf_hi(w.z), s, acc[5]);
  acc[6] = fmaf(bf_lo(w.w), s, acc[6]); acc[7] = fmaf(bf_hi(w.w), s, acc[7]);
}
__device__ __forceinline__ float warp_red8(float* v, int lane) {
  bool b4 = lane & 16, b3 = lane & 8, b2 = lane & 4;
  float t[4];
#pragma unroll
  for (int i = 0; i < 4; i++) { float keepv = b4 ? v[i + 4] : v[i], send = b4 ? v[i] : v[i + 4]; t[i] = keepv + __shfl_xor_sync(~0u, send, 16); }
  float u[2];
#pragma unroll
  for (int i = 0; i < 2; i++) { float keepv = b3 ? t[i + 2] : t[i], send = b3 ? t[i] : t[i + 2]; u[i] = keepv + __shfl_xor_sync(~0u, send, 8); }
  float keepv = b2 ? u[1] : u[0], send = b2 ? u[0] : u[1];
  float r = keepv + __shfl_xor_sync(~0u, send, 4);
  r += __shfl_xor_sync(~0u, r, 2);
  r += __shfl_xor_sync(~0u, r, 1);
  return r;
}
__device__ __forceinline__ void mod_unit_warp(const Params& P, int u, int lane, uint32_t tag) {
  float acc[8] = {0, 0, 0, 0, 0, 0, 0, 0};
#pragma unroll 1
  for (int i = 0; i < 14; i += 2) {
    int k0 = i * 32 + lane, k1 = k0 + 32;
    uint4 w0 = __ldg((const uint4*)(P.pwmod + (size_t)k0 * 2688 + u * 8));
    uint4 w1 = __ldg((const uint4*)(P.pwmod + (size_t)k1 * 2688 + u * 8));
    float c0 = __bfloat162float(P.pc[k0]), c1 = __bfloat162float(P.pc[k1]);
    fma8(acc, w0, silu_bf(c0));
    fma8(acc, w1, silu_bf(c1));
  }
  float r = warp_red8(acc, lane);
  if ((lane & 3) == 0) st_relaxed(&g_mod[u * 8 + (lane >> 2)], (pack2(r, 0.f) & 0xFFFFu) | tag);
}
__device__ __forceinline__ uint4 poll_mod42(int idx, uint32_t tag, uint32_t ab) {
  uint4 v; uint32_t n = 0;
  while (true) {
    v = ld_relaxed4(&g_mod[idx]);
    if ((((v.x ^ tag) | (v.y ^ tag) | (v.z ^ tag) | (v.w ^ tag)) >> 16) == 0) break;
    if (give_up(n, ab)) break;
  }
  return v;
}
__device__ __forceinline__ void put_mod4(uint32_t base, int k, uint4 v, bool add1) {
  float f0 = bf_lo(v.x), f1 = bf_lo(v.y), f2 = bf_lo(v.z), f3 = bf_lo(v.w);
  if (add1) { f0 += 1.f; f1 += 1.f; f2 += 1.f; f3 += 1.f; }
  sts32(base + perm448(k) * 2, pack2(f0, f1));
  sts32(base + perm448(k + 2) * 2, pack2(f2, f3));
}

__global__ void __cluster_dims__(2, 1, 1) __launch_bounds__(384, 1) fused_kernel(const __grid_constant__ Params P) {
  extern __shared__ __align__(1024) uint8_t smem_raw[];
  const uint32_t sb = smem_u32(smem_raw);
  const int tid = threadIdx.x, lane = tid & 31, warp = __shfl_sync(~0u, tid >> 5, 0);
  const int b = blockIdx.x, rb = b >> 3, c8 = b & 7, cb4 = c8 >> 1, kh = c8 & 1;
  const int h3 = 2 * rb + (cb4 & 1), c4 = 2 * (cb4 >> 1) + kh;
  auto BAR = [&](int i) { return sb + OFF_BAR + 8u * i; };
  auto PAGE = [&](int i) { return sb + PG * i; };
  auto mbar_wait = [&](uint32_t bar) { mbar_wait2(bar, sb + OFF_ABORT); };
  auto poll = [&](int c, uint32_t target) { poll2(c, target, sb + OFF_ABORT); };
  auto poll_mod4 = [&](int idx, uint32_t tg) { return poll_mod42(idx, tg, sb + OFF_ABORT); };

  STAMP(0);
  const uint32_t ep = ld_relaxed(&g_epoch) + 1;
  const uint32_t tag = ep << 16;
  uint4 mw0 = make_uint4(0, 0, 0, 0), mw1 = mw0; float mc0 = 0.f, mc1 = 0.f;
  if (warp < 8 && b < 112) {
    mw0 = __ldg((const uint4*)(P.pwmod + (size_t)tid * 2688 + b * 8));
    mc0 = __bfloat162float(P.pc[tid]);
    if (tid < 192) { mw1 = __ldg((const uint4*)(P.pwmod + (size_t)(tid + 256) * 2688 + b * 8)); mc1 = __bfloat162float(P.pc[tid + 256]); }
  }
  if (warp == 8) {
    if (lane == 0) sts32(sb + OFF_ABORT, (sb & 1023u) ? 0x40000u : 0u);
    for (int i = lane; i < B_COUNT; i += 32) {
      uint32_t cnt = 1;
      if (i >= B_S5F && i < B_S5F + 16) cnt = 3;
      else if (i == B_XFREE || i == B_KPASS || i == B_VPASS || i == B_QPASS || i == B_ATT || i == B_Z2PASS || (i >= B_Z1C && i < B_Z1C + 3) ||
               (i >= B_S5E && i < B_S5E + 16) || i == B_X5FREE || i == B_X6FREE) cnt = 8;
      else if (i == B_S3MMA || (i >= B_A4RD && i < B_A4RD + 2) || (i >= B_STG && i < B_STG + 2) || (i >= B_A6RD && i < B_ST1)) cnt = 4;
      else if (i == B_STGDONE) cnt = 2;
      mbar_init(BAR(i), cnt);
    }
    __syncwarp();
    if (lane == 0) {
      mbar_expect(BAR(B_XB5), 14336); mbar_expect(BAR(B_XB5 + 1), 14336);
      mbar_expect(BAR(B_XB6), 7168); mbar_expect(BAR(B_XB6 + 1), 7168);
    }
    asm volatile("fence.mbarrier_init.release.cluster;" ::: "memory");
  } else if (warp == 9 && lane == 0) {
    prefetch_map(&P.x); prefetch_map(&P.wqkv);
  }
  __syncthreads();
  asm volatile("barrier.cluster.arrive.release.aligned;" ::: "memory");

  if (warp >= 8) {
    asm volatile("setmaxnreg.dec.sync.aligned.u32 40;");
    if (warp == 8) {
      if (lane == 0) {
        auto ldqkv = [&](int part, int c, int page, int bar) {
          mbar_expect(BAR(bar), 7168);
          tma2d(PAGE(page), &P.wqkv, part * DM + 56 * c8, 64 * c, BAR(bar));
        };
        auto ldw = [&](const CUtensorMap* m64, const CUtensorMap* m48, int col, int c, int p0, int p1, int bar) {
          mbar_expect(BAR(bar), 14336);
          tma2d(PAGE(p0), m64, col, 64 * c, BAR(bar));
          tma2d(PAGE(p1), m48, col + 64, 64 * c, BAR(bar));
        };
        for (int c = 0; c < 7; c++) ldqkv(1, c, 14 + c, B_WK + c);
        for (int c = 0; c < 6; c++) ldqkv(2, c, 21 + c, B_WV + c);
        prefetch_map(&P.wo64); prefetch_map(&P.wo48); prefetch_map(&P.win64); prefetch_map(&P.win48); prefetch_map(&P.wsp); prefetch_map(&P.wout);
        mbar_wait(BAR(B_XFREE));
        ldqkv(2, 6, 7, B_WV + 6);
        for (int c = 0; c < 7; c++) ldqkv(0, c, c, B_WQ + c);
        mbar_wait(BAR(B_VPASS));
        for (int c = 0; c < 3; c++) ldw(&P.wo64, &P.wo48, 112 * c4, c, 20 + 2 * c, 21 + 2 * c, B_WO + c);
        mbar_wait(BAR(B_QPASS));
        for (int c = 3; c < 7; c++) ldw(&P.wo64, &P.wo48, 112 * c4, c, 2 * c - 6, 2 * c - 5, B_WO + c);
        const int z2col = FH + 112 * c8, z1col = 112 * c8;
        mbar_wait(BAR(B_ATT));
        ldw(&P.win64, &P.win48, z2col, 0, 16, 17, B_Z2W + 0);
        ldw(&P.win64, &P.win48, z2col, 1, 18, 19, B_Z2W + 1);
        ldw(&P.win64, &P.win48, z2col, 2, 15, 26, B_Z2W + 2);
        mbar_wait(BAR(B_S3MMA));
        for (int c = 3; c < 6; c++) ldw(&P.win64, &P.win48, z2col, c, 14 + 2 * c, 15 + 2 * c, B_Z2W + c);
        mbar_wait(BAR(B_A4E));
        ldw(&P.win64, &P.win48, z2col, 6, 0, 1, B_Z2W + 6);
        mbar_wait(BAR(B_A4RD));
        ldw(&P.win64, &P.win48, z1col, 0, 4, 5, B_Z1W + 0);
        ldw(&P.win64, &P.win48, z1col, 1, 6, 14, B_Z1W + 1);
        mbar_wait(BAR(B_A4RD + 1));
        ldw(&P.win64, &P.win48, z1col, 2, 9, 10, B_Z1W + 2);
        ldw(&P.win64, &P.win48, z1col, 3, 11, 12, B_Z1W + 3);
        mbar_wait(BAR(B_Z2PASS));
        ldw(&P.win64, &P.win48, z1col, 4, 16, 17, B_Z1W + 4);
        ldw(&P.win64, &P.win48, z1col, 5, 18, 19, B_Z1W + 5);
        ldw(&P.win64, &P.win48, z1col, 6, 0, 1, B_Z1W + 6);
        for (int i = 0; i < 16; i++) {
          int s = i & 3;
          if (i == 1) mbar_wait(BAR(B_STGDONE));
          if (i >= 4) mbar_wait(BAR(B_S5E + i - 4)); else if (i >= 1) mbar_wait(BAR(B_Z1C + i - 1));
          int hl = i < 8 ? 2 * i : 2 * i - 15;
          mbar_expect(BAR(B_S5F + i), 16384);
          tma2d(PAGE(s == 0 ? 20 : 6 * s - 4), &P.wsp, 1024 * kh + 64 * hl, 128 * rb, BAR(B_S5F + i));
        }
        for (int c = 0; c < 7; c++) {
          if (c == 0) mbar_wait(BAR(B_S5E + 13));
          if (c == 3) mbar_wait(BAR(B_S5E + 14));
          if (c == 6) mbar_wait(BAR(B_S5E + 15));
          mbar_expect(BAR(B_B6 + c), 14336);
          tma2d(PAGE(2 + 2 * c), &P.wout, 112 * cb4 + 56 * (1 - kh), 448 * kh + 64 * c, BAR(B_B6 + c));
          tma2d(PAGE(3 + 2 * c), &P.wout, 112 * cb4 + 56 * kh, 448 * kh + 64 * c, BAR(B_B6 + c));
        }
      }
    } else if (warp == 9) {
      if (lane == 0) {
        for (int c = 0; c < 7; c++) { mbar_expect(BAR(B_X + c), 16384); tma2d(PAGE(2 * c), &P.x, 64 * c, 128 * rb, BAR(B_X + c)); }
        prefetch_map(&P.o); prefetch_map(&P.x1); prefetch_map(&P.u);
      }
#pragma unroll 1
      for (int kv = 0; kv < 2; kv++) {
        const uint32_t dst = PAGE(kv ? 14 : 8), bar = BAR(kv ? B_VREM : B_KREM);
        mbar_wait(BAR(kv ? B_KPASS : B_XFREE));
        if (rb < 2) {
          int n16 = (2 - rb) * 1024;
          for (int i = lane; i < n16; i += 32) sts128(dst + i * 16, make_uint4(0, 0, 0, 0));
          fence_async_smem();
          __syncwarp();
        }
        if (lane == 0) {
          if (rb == 0) mbar_arrive(bar);
          else {
            mbar_expect(bar, rb >= 2 ? 32768 : 16384);
            for (int d = 1; d <= 2 && d <= rb; d++) {
              poll((kv ? C_V : C_K) + (rb - d) * 8 + c8, 2 * ep);
              fence_async_glob();
              bulk_ld(dst + (2 - d) * 16384, g_kv + (size_t)(((rb - d) * 8 + c8) * 2 + kv) * 16384, 16384, bar);
            }
          }
        }
        __syncwarp();
      }
      if (lane == 0) {
        mbar_wait(BAR(B_ATT));
        poll(C_O + h3, 8 * ep);
        fence_async_glob();
        for (int c = 0; c < 7; c++) { mbar_expect(BAR(B_A3 + c), 8192); tma2d(PAGE(8 + c), &P.o, 64 * c, 64 * h3, BAR(B_A3 + c)); }
        mbar_wait(BAR(B_S3MMA));
        for (int a = 0; a < 2; a++) {
          poll(C_X + 2 * rb + a, 4 * ep);
          fence_async_glob();
          for (int c = 0; c < 7; c++) { mbar_expect(BAR(B_A4 + 7 * a + c), 8192); tma2d(PAGE(7 * a + c), &P.x1, 64 * c, 128 * rb + 64 * a, BAR(B_A4 + 7 * a + c)); }
        }
        mbar_wait(BAR(B_Z2PASS));
        for (int i = 0; i < 16; i++) {
          int s = i & 3;
          if (i == 1) mbar_wait(BAR(B_STGDONE));
          if (i >= 4) mbar_wait(BAR(B_S5E + i - 4)); else if (i >= 1) mbar_wait(BAR(B_Z1C + i - 1));
          int h = 16 * kh + (i < 8 ? 2 * i : 2 * i - 15);
          poll(C_Z + h, 8 * ep);
          fence_async_glob();
          uint32_t dst = PAGE(s == 0 ? 22 : 6 * s - 2);
          mbar_expect(BAR(B_S5F + i), 28672);
          bulk_ld(dst, g_z2t + ((size_t)h * FH + 112 * c8) * 128, 14336, BAR(B_S5F + i));
          bulk_ld(dst + 14336, g_z2t + ((size_t)h * FH + 112 * (c8 ^ 1)) * 128, 14336, BAR(B_S5F + i));
        }
        mbar_wait(BAR(B_S5E + 12));
        mbar_wait(BAR(B_S5E + 15));
        for (int a = 0; a < 2; a++) {
          poll(C_U + (2 * rb + a) * 2 + kh, 4 * ep);
          fence_async_glob();
          for (int c = 0; c < 5; c++) {
            if (a == 1 && c == 4) mbar_wait(BAR(B_XRD));
            mbar_expect(BAR(B_A6 + 7 * a + c), 8192);
            tma2d(PAGE(16 + 5 * a + c), &P.u, 448 * kh + 64 * c, 128 * rb + 64 * a, BAR(B_A6 + 7 * a + c));
          }
        }
        for (int a = 0; a < 2; a++)
          for (int c = 5; c < 7; c++) {
            mbar_wait(BAR(B_A6RD + 2 * a + c - 5));
            mbar_expect(BAR(B_A6 + 7 * a + c), 8192);
            tma2d(PAGE(16 + 5 * a + c - 5), &P.u, 448 * kh + 64 * c, 128 * rb + 64 * a, BAR(B_A6 + 7 * a + c));
          }
      }
    } else {
      const int a = warp - 10;
      if (a == 0) mod_unit_warp(P, 112 + b, lane, tag);
      else {
        if (b < 96) mod_unit_warp(P, 240 + b, lane, tag);
        if (lane == 0) {
          mbar_wait(BAR(B_X + 6));
          l2_prefetch((const uint8_t*)P.pwo + b * 3136, 3136);
          l2_prefetch((const uint8_t*)P.pwin + b * 12544, 12544);
          for (int i = 0; i < 4; i++) l2_prefetch((const uint8_t*)P.pwsp + (size_t)b * 65536 + i * 16384, 16384);
          l2_prefetch((const uint8_t*)P.pwout + b * 6272, 6272);
        }
      }
      if (lane == 0) {
        for (int kv = 0; kv < 2; kv++) {
          mbar_wait(BAR((kv ? B_VRDY : B_KRDY) + a));
          bulk_st(g_kv + (size_t)((rb * 8 + c8) * 2 + kv) * 16384 + a * 8192, PAGE((kv ? 18 : 12) + a), 8192);
          publish((kv ? C_V : C_K) + rb * 8 + c8);
        }
      }
      __syncwarp();
      if (a == 0) {
        for (int i = lane; i < 224; i += 32) {
          uint4 v = poll_mod4(1344 + i * 4, tag);
          bool isc = i >= 112;
          put_mod4(sb + OFF_MOD2 + (isc ? 0 : 896), (isc ? i - 112 : i) * 4, v, isc);
        }
        if (lane < 28) {
          uint4 v = poll_mod4(896 + 112 * c4 + lane * 4, tag);
          sts128(sb + OFF_GA + lane * 16, make_uint4(v.x << 16, v.y << 16, v.z << 16, v.w << 16));
        }
        if (lane < 14) {
          uint4 v = poll_mod4(2240 + 56 * c8 + lane * 4, tag);
          sts128(sb + OFF_GB + lane * 16, make_uint4(v.x << 16, v.y << 16, v.z << 16, v.w << 16));
        }
        warp_arrive(BAR(B_MOD2), lane);
      }
      if (lane == 0) poll(C_X + 2 * rb + a, 4 * ep);
      __syncwarp();
#pragma unroll 1
      for (int i = 0; i < 2; i++) {
        int r = lane + 32 * i;
        const float4* p = (const float4*)(g_st1 + (size_t)(128 * rb + 64 * a + r) * 4);
        float4 p0 = __ldcg(p), p1 = __ldcg(p + 1);
        float mean = (p0.x + p0.z + p1.x + p1.z) * (1.f / 448.f);
        float d0 = p0.x * (1.f / 112.f) - mean, d1 = p0.z * (1.f / 112.f) - mean, d2 = p1.x * (1.f / 112.f) - mean, d3 = p1.z * (1.f / 112.f) - mean;
        float m2 = p0.y + p0.w + p1.y + p1.w + 112.f * (d0 * d0 + d1 * d1 + d2 * d2 + d3 * d3);
        float rstd = rsqrtf(m2 * (1.f / 448.f) + 1e-5f);
        sts32f(sb + OFF_ST1 + (64 * a + r) * 8, rstd);
        sts32f(sb + OFF_ST1 + (64 * a + r) * 8 + 4, -mean * rstd);
      }
      warp_arrive(BAR(B_ST1 + a), lane);
      if (lane == 0) {
        mbar_wait(BAR(B_STG + a));
        bulk_st(g_z2t + ((size_t)(2 * rb + a) * FH + 112 * c8) * 128, PAGE(a ? 7 : 2), 14336);
        publish(C_Z + 2 * rb + a);
        mbar_arrive(BAR(B_STGDONE));
        mbar_wait(BAR(B_A4RD + 1));
      }
      __syncwarp();
#pragma unroll 1
      for (int i = 8 * a; i < 8 * a + 8; i++) {
        int hl = i < 8 ? 2 * i : 2 * i - 15;
        if (lane == 0) poll(C_Z + 16 * kh + hl, 8 * ep);
        __syncwarp();
#pragma unroll 1
        for (int q = 0; q < 2; q++) {
          int r = lane + 32 * q;
          const float4* p = (const float4*)(g_st2 + (size_t)((16 * kh + hl) * 64 + r) * 8);
          float4 p0 = __ldcg(p), p1 = __ldcg(p + 1), p2 = __ldcg(p + 2), p3 = __ldcg(p + 3);
          float mean = (p0.x + p0.z + p1.x + p1.z + p2.x + p2.z + p3.x + p3.z) * (1.f / 896.f);
          float m2 = p0.y + p0.w + p1.y + p1.w + p2.y + p2.w + p3.y + p3.w, d, e = 0.f;
          d = p0.x * (1.f / 112.f) - mean; e = fmaf(d, d, e); d = p0.z * (1.f / 112.f) - mean; e = fmaf(d, d, e);
          d = p1.x * (1.f / 112.f) - mean; e = fmaf(d, d, e); d = p1.z * (1.f / 112.f) - mean; e = fmaf(d, d, e);
          d = p2.x * (1.f / 112.f) - mean; e = fmaf(d, d, e); d = p2.z * (1.f / 112.f) - mean; e = fmaf(d, d, e);
          d = p3.x * (1.f / 112.f) - mean; e = fmaf(d, d, e); d = p3.z * (1.f / 112.f) - mean; e = fmaf(d, d, e);
          float rstd = rsqrtf(fmaf(112.f, e, m2) * (1.f / 896.f) + 1e-5f);
          int pos = i * 64 + perm64(r);
          sts16(sb + OFF_R5 + pos * 2, pack2(rstd, 0.f));
          sts32f(sb + OFF_MU5 + pos * 4, mean);
        }
        warp_arrive(BAR(B_S5F + i), lane);
      }
    }
    __syncwarp();
    asm volatile("barrier.cluster.wait.acquire.aligned;" ::: "memory");
  } else {
    asm volatile("setmaxnreg.inc.sync.aligned.u32 232;");
    const int a = warp >> 2, w = warp & 3, j = lane & 3, g = lane >> 2, t128 = tid & 127;
    const int r0 = 16 * w + g;
    const uint32_t lds_off = (16 * w + (lane & 15)) * 128, lx = lane & 7, lhi = lane >> 4;
    auto LDA = [&](uint32_t page, int ks) { return page + lds_off + ((((uint32_t)(2 * ks) + lhi) ^ lx) << 4); };
    const uint32_t peer = kh ^ 1;
    const uint32_t dbase = (sb & 0x3FFFFu) >> 4;
    auto desc = [&](uint32_t off, uint32_t lbo) { return mkdesc(dbase, off, lbo); };

    if (b < 112) {
      float acc[8] = {0, 0, 0, 0, 0, 0, 0, 0};
      fma8(acc, mw0, silu_bf(mc0));
      fma8(acc, mw1, silu_bf(mc1));
      float r = warp_red8(acc, lane);
      if (j == 0) sts32f(sb + OFF_RED + (warp * 8 + g) * 4, r);
      bar_sync(1, 256);
      if (tid < 8) {
        float s = 0.f;
#pragma unroll
        for (int i = 0; i < 8; i++) s += lds32f(sb + OFF_RED + (i * 8 + tid) * 4);
        st_relaxed(&g_mod[b * 8 + tid], (pack2(s, 0.f) & 0xFFFFu) | tag);
      }
    }
    STAMP(1);
    if (a == 1) bar_arrive(4, 256);

    uint32_t qf[7][2];
    {
      uint32_t A[28][4];
      float s4[4][4] = {};
#pragma unroll
      for (int c = 0; c < 7; c++) {
        mbar_wait(BAR(B_X + c));
#pragma unroll
        for (int ks = 0; ks < 4; ks++) { ldsm4(A[4 * c + ks], LDA(PAGE(2 * c + a), ks)); rowsum_mma(s4[ks], A[4 * c + ks]); }
      }
      warp_arrive(BAR(B_XFREE), lane);
      STAMP(2);
      {
        float m0 = (s4[0][0] + s4[1][0] + s4[2][0] + s4[3][0]) * (1.f / 448.f), m1 = (s4[0][2] + s4[1][2] + s4[2][2] + s4[3][2]) * (1.f / 448.f);
        uint32_t mp0 = pack2(m0, m0), mp1 = pack2(m1, m1);
        float q4[4][4] = {};
#pragma unroll
        for (int i = 0; i < 28; i++) {
          A[i][0] = hsub2(A[i][0], mp0); A[i][1] = hsub2(A[i][1], mp1); A[i][2] = hsub2(A[i][2], mp0); A[i][3] = hsub2(A[i][3], mp1);
          uint32_t sq[4] = {hmul2(A[i][0], A[i][0]), hmul2(A[i][1], A[i][1]), hmul2(A[i][2], A[i][2]), hmul2(A[i][3], A[i][3])};
          rowsum_mma(q4[i & 3], sq);
        }
        float e0 = m0 - bf_lo(mp0), e1 = m1 - bf_lo(mp1);
        float v0 = (q4[0][0] + q4[1][0] + q4[2][0] + q4[3][0]) * (1.f / 448.f) - e0 * e0, v1 = (q4[0][2] + q4[1][2] + q4[2][2] + q4[3][2]) * (1.f / 448.f) - e1 * e1;
        float rs0 = rsqrtf(fmaxf(v0, 0.f) + 1e-5f), rs1 = rsqrtf(fmaxf(v1, 0.f) + 1e-5f);
        uint32_t rp0 = pack2(rs0, rs0), rp1 = pack2(rs1, rs1);
#pragma unroll
        for (int i = 0; i < 28; i++) {
          A[i][0] = hmul2(A[i][0], rp0); A[i][1] = hmul2(A[i][1], rp1); A[i][2] = hmul2(A[i][2], rp0); A[i][3] = hmul2(A[i][3], rp1);
        }
      }
      STAMP(3);
      if (tid < 224) {
        uint4 v = poll_mod4(tid * 4, tag);
        bool isc = tid >= 112;
        put_mod4(sb + OFF_MOD1 + (isc ? 0 : 896), (isc ? tid - 112 : tid) * 4, v, isc);
      }
      bar_sync(1, 256);
      STAMP(4);
      const uint32_t st_row = 16 * w + ((lane >> 3) & 1) * 8 + (lane & 7), st_hi = lane >> 4;
      auto store_tile = [&](const float* acc, uint32_t page) {
#pragma unroll
        for (int t = 0; t < 8; t += 2) {
          uint32_t addr = page + st_row * 128 + ((((uint32_t)t + st_hi) ^ lx) << 4);
          uint32_t r2 = t < 6 ? pack2(acc[4 * t + 4], acc[4 * t + 5]) : 0u, r3 = t < 6 ? pack2(acc[4 * t + 6], acc[4 * t + 7]) : 0u;
          stsm4(addr, pack2(acc[4 * t], acc[4 * t + 1]), pack2(acc[4 * t + 2], acc[4 * t + 3]), r2, r3);
        }
        fence_async_smem();
      };
      float acc[28];
      bar_sync(4 + a, 256);
#pragma unroll
      for (int c = 0; c < 7; c++) {
#pragma unroll
        for (int h = 0; h < 2; h++) {
          uint4 cv = lds128(sb + OFF_MOD1 + ((2 * c + h) * 4 + j) * 16), sv = lds128(sb + OFF_MOD1 + 896 + ((2 * c + h) * 4 + j) * 16);
          uint32_t* p = A[4 * c + 2 * h]; uint32_t* q = A[4 * c + 2 * h + 1];
          p[0] = hfma2(p[0], cv.x, sv.x); p[1] = hfma2(p[1], cv.x, sv.x); p[2] = hfma2(p[2], cv.y, sv.y); p[3] = hfma2(p[3], cv.y, sv.y);
          q[0] = hfma2(q[0], cv.z, sv.z); q[1] = hfma2(q[1], cv.z, sv.z); q[2] = hfma2(q[2], cv.w, sv.w); q[3] = hfma2(q[3], cv.w, sv.w);
        }
        mbar_wait(BAR(B_WK + c));
        wg_fence();
#pragma unroll
        for (int ks = 0; ks < 4; ks++) wg_rs56<1>(acc, A[4 * c + ks], desc(PG * (14 + c) + ks * 2048, 0), (c | ks) != 0);
      }
      wg_commit();
      bar_arrive(5 - a, 256);
      wg_wait<0>(); keep<28>(acc);
      warp_arrive(BAR(B_KPASS), lane);
      store_tile(acc, PAGE(12 + a));
      warp_arrive(BAR(B_KRDY + a), lane);
      STAMP(5);
      bar_sync(4 + a, 256);
#pragma unroll
      for (int c = 0; c < 7; c++) {
        mbar_wait(BAR(B_WV + c));
        wg_fence();
#pragma unroll
        for (int ks = 0; ks < 4; ks++) wg_rs56<1>(acc, A[4 * c + ks], desc(PG * (c < 6 ? 21 + c : 7) + ks * 2048, 0), (c | ks) != 0);
      }
      wg_commit();
      bar_arrive(5 - a, 256);
      wg_wait<0>(); keep<28>(acc);
      warp_arrive(BAR(B_VPASS), lane);
      mbar_wait(BAR(B_KPASS));
      store_tile(acc, PAGE(18 + a));
      warp_arrive(BAR(B_VRDY + a), lane);
      STAMP(6);
      bar_sync(4 + a, 256);
#pragma unroll
      for (int c = 0; c < 7; c++) {
        mbar_wait(BAR(B_WQ + c));
        wg_fence();
#pragma unroll
        for (int ks = 0; ks < 4; ks++) wg_rs56<1>(acc, A[4 * c + ks], desc(PG * (c) + ks * 2048, 0), (c | ks) != 0);
      }
      wg_commit();
      if (a == 0) bar_arrive(5, 256);
      wg_wait<0>(); keep<28>(acc);
      warp_arrive(BAR(B_QPASS), lane);
#pragma unroll
      for (int t = 0; t < 7; t++) { qf[t][0] = pack2(acc[4 * t], acc[4 * t + 1]); qf[t][1] = pack2(acc[4 * t + 2], acc[4 * t + 3]); }
    }
    STAMP(7);
    {
      const uint32_t kb = (8 + a) * PG, vb = (14 + a) * PG;
      const int q0 = 128 * rb + 64 * a;
      const float sc = 0.18898223650461362f * 1.4426950408889634f;
      __nv_bfloat16* orow = g_o + (size_t)(q0 + r0) * DM + 56 * c8 + 2 * j;
      const int dd = r0 - 2 * j;
      mbar_wait(BAR(B_KRDY)); mbar_wait(BAR(B_KRDY + 1)); mbar_wait(BAR(B_KREM));
      STAMP(8);
      uint32_t o3[2];
#pragma unroll
      for (int hd = 0; hd < 2; hd++) {
        float sm[96], s0[32], s4[32];
        uint32_t qa[2][4];
        if (hd == 0) {
          qa[0][0] = qf[0][0]; qa[0][1] = qf[0][1]; qa[0][2] = qf[1][0]; qa[0][3] = qf[1][1];
          qa[1][0] = qf[2][0]; qa[1][1] = qf[2][1]; qa[1][2] = j < 2 ? qf[3][0] : 0u; qa[1][3] = j < 2 ? qf[3][1] : 0u;
        } else {
          qa[0][0] = j < 2 ? 0u : qf[3][0]; qa[0][1] = j < 2 ? 0u : qf[3][1]; qa[0][2] = qf[4][0]; qa[0][3] = qf[4][1];
          qa[1][0] = qf[5][0]; qa[1][1] = qf[5][1]; qa[1][2] = qf[6][0]; qa[1][3] = qf[6][1];
        }
        wg_fence();
#pragma unroll
        for (int ks = 0; ks < 2; ks++) {
          uint32_t ko = hd * 48 + ks * 32;
          wg_rs64<0>(s0, qa[ks], desc(kb + ko, 16), ks);
          wg_rs64<0>(s4, qa[ks], desc(kb + 4 * PG + ko, 16), ks);
          wg_rs192<0>(sm, qa[ks], desc(kb + PG + ko, 16), ks);
        }
        wg_commit();
        wg_wait<0>(); keep<96>(sm); keep<32>(s0); keep<32>(s4);
        if (q0 < 256) {
          const float ninf = __int_as_float(0xff800000);
#pragma unroll
          for (int i = 0; i < 32; i++) s0[i] = ninf;
#pragma unroll
          for (int i = 0; i < 96; i++) if (q0 - 192 + 64 * (i >> 5) < 0) sm[i] = ninf;
        }
#pragma unroll
        for (int i = 0; i < 32; i++) { int t = i >> 2, e = (i >> 1) & 1, f = i & 1; s4[i] = (8 * t + f - 8 * e <= dd) ? s4[i] : s0[i]; }
        float mx0 = s4[0], mx1 = s4[2];
#pragma unroll
        for (int i = 0; i < 32; i++) { if (i & 2) mx1 = fmaxf(mx1, s4[i]); else mx0 = fmaxf(mx0, s4[i]); }
#pragma unroll
        for (int i = 0; i < 96; i++) { if (i & 2) mx1 = fmaxf(mx1, sm[i]); else mx0 = fmaxf(mx0, sm[i]); }
        mx0 = quad_max(mx0) * sc; mx1 = quad_max(mx1) * sc;
        float l0 = 0.f, l1 = 0.f;
        uint32_t pm[48], p0[16], p4[16];
#pragma unroll
        for (int i = 0; i < 48; i++) {
          float m = (i & 1) ? mx1 : mx0;
          float x = ex2(fmaf(sm[2 * i], sc, -m)), y = ex2(fmaf(sm[2 * i + 1], sc, -m));
          if (i & 1) l1 += x + y; else l0 += x + y;
          pm[i] = pack2(x, y);
        }
#pragma unroll
        for (int i = 0; i < 16; i++) {
          float m = (i & 1) ? mx1 : mx0;
          float x = ex2(fmaf(s4[2 * i], sc, -m)), y = ex2(fmaf(s4[2 * i + 1], sc, -m));
          if (i & 1) l1 += x + y; else l0 += x + y;
          uint32_t pw = pack2(x, y);
          int lim = 8 * (i >> 1) - 8 * (i & 1);
          uint32_t mk = (lim + 1 <= dd) ? 0xFFFFFFFFu : (lim <= dd ? 0x0000FFFFu : 0u);
          p4[i] = pw & mk; p0[i] = pw & ~mk;
        }
        if (hd == 0) { mbar_wait(BAR(B_VRDY)); mbar_wait(BAR(B_VRDY + 1)); mbar_wait(BAR(B_VREM)); }
        float o[16];
        wg_fence();
        const uint32_t vo = vb + hd * 48;
#pragma unroll
        for (int s = 0; s < 12; s++) wg_rs32<1>(o, pm + 4 * s, desc(vo + PG + s * 2048, 0), s);
#pragma unroll
        for (int s = 0; s < 4; s++) wg_rs32<1>(o, p0 + 4 * s, desc(vo + s * 2048, 0), 1);
#pragma unroll
        for (int s = 0; s < 4; s++) wg_rs32<1>(o, p4 + 4 * s, desc(vo + 4 * PG + s * 2048, 0), 1);
        wg_commit();
        l0 = 1.f / quad_sum(l0); l1 = 1.f / quad_sum(l1);
        wg_wait<0>(); keep<16>(o);
        if (hd == 1) warp_arrive(BAR(B_ATT), lane);
#pragma unroll
        for (int t = 0; t < 4; t++) {
          uint32_t v0 = pack2(o[4 * t] * l0, o[4 * t + 1] * l0), v1 = pack2(o[4 * t + 2] * l1, o[4 * t + 3] * l1);
          if (hd == 0 && t == 3) { o3[0] = v0; o3[1] = v1; continue; }
          if (hd == 1 && t == 0) { v0 = j < 2 ? o3[0] : v0; v1 = j < 2 ? o3[1] : v1; }
          *(uint32_t*)(orow + hd * 24 + 8 * t) = v0;
          *(uint32_t*)(orow + 8 * DM + hd * 24 + 8 * t) = v1;
        }
      }
      bar_sync(2 + a, 128);
      if (t128 == 0) publish(C_O + 2 * rb + a);
    }
    STAMP(9);
    if (a == (cb4 & 1)) {
      const size_t off = (size_t)(64 * h3 + r0) * DM + 112 * c4 + 2 * j;
      uint32_t xr[28];
#pragma unroll
      for (int t = 0; t < 14; t++) { xr[2 * t] = __ldg((const uint32_t*)(P.px + off + 8 * t)); xr[2 * t + 1] = __ldg((const uint32_t*)(P.px + off + 8 * DM + 8 * t)); }
      float acc[56];
#pragma unroll
      for (int c = 0; c < 7; c++) {
        mbar_wait(BAR(B_WO + c));
        mbar_wait(BAR(B_A3 + c));
        if (c == 0) STAMP(10);
        wg_fence();
#pragma unroll
        for (int ks = 0; ks < 4; ks++) wg_ss112<1>(acc, desc(PG * (8 + c) + ks * 32, 16), desc(PG * (c < 3 ? 20 + 2 * c : 2 * c - 6) + ks * 2048, PG), (c | ks) != 0);
      }
      wg_commit();
      mbar_wait(BAR(B_MOD2));
      wg_wait<0>(); keep<56>(acc);
      warp_arrive(BAR(B_S3MMA), lane);
      float s0 = 0.f, s1 = 0.f;
#pragma unroll
      for (int t = 0; t < 14; t++) {
        float2 ga = lds64f(sb + OFF_GA + (8 * t + 2 * j) * 4);
        uint32_t v0 = pack2(fmaf(ga.x, acc[4 * t], bf_lo(xr[2 * t])), fmaf(ga.y, acc[4 * t + 1], bf_hi(xr[2 * t])));
        uint32_t v1 = pack2(fmaf(ga.x, acc[4 * t + 2], bf_lo(xr[2 * t + 1])), fmaf(ga.y, acc[4 * t + 3], bf_hi(xr[2 * t + 1])));
        *(uint32_t*)(g_x1 + off + 8 * t) = v0;
        *(uint32_t*)(g_x1 + off + 8 * DM + 8 * t) = v1;
        acc[4 * t] = bf_lo(v0); acc[4 * t + 1] = bf_hi(v0); acc[4 * t + 2] = bf_lo(v1); acc[4 * t + 3] = bf_hi(v1);
        s0 += acc[4 * t] + acc[4 * t + 1]; s1 += acc[4 * t + 2] + acc[4 * t + 3];
      }
      s0 = quad_sum(s0); s1 = quad_sum(s1);
      float m0 = s0 * (1.f / 112.f), m1 = s1 * (1.f / 112.f), q0 = 0.f, q1 = 0.f;
#pragma unroll
      for (int t = 0; t < 14; t++) {
        float d;
        d = acc[4 * t] - m0; q0 = fmaf(d, d, q0); d = acc[4 * t + 1] - m0; q0 = fmaf(d, d, q0);
        d = acc[4 * t + 2] - m1; q1 = fmaf(d, d, q1); d = acc[4 * t + 3] - m1; q1 = fmaf(d, d, q1);
      }
      q0 = quad_sum(q0); q1 = quad_sum(q1);
      if (j == 0) { g_st1[(size_t)(64 * h3 + r0) * 4 + c4] = make_float2(s0, q0); g_st1[(size_t)(64 * h3 + r0 + 8) * 4 + c4] = make_float2(s1, q1); }
      bar_sync(2 + a, 128);
      if (t128 == 0) publish(C_X + h3);
    }
    STAMP(11);
    uint32_t z1p[28];
    {
      uint32_t A[28][4];
      float acc[56];
      mbar_wait(BAR(B_MOD2));
      mbar_wait(BAR(B_ST1 + a));
      const float2 st0 = lds64f(sb + OFF_ST1 + (64 * a + r0) * 8), st1 = lds64f(sb + OFF_ST1 + (64 * a + r0 + 8) * 8);
#pragma unroll
      for (int c = 0; c < 7; c++) {
        mbar_wait(BAR(B_A4 + 7 * a + c));
        if (c == 0) STAMP(12);
#pragma unroll
        for (int ks = 0; ks < 4; ks++) ldsm4(A[4 * c + ks], LDA(PAGE(7 * a + c), ks));
        if (c == 6) warp_arrive(BAR(B_A4RD + a), lane);
        if (c == 1 && a == 0) warp_arrive(BAR(B_A4E), lane);
#pragma unroll
        for (int h = 0; h < 2; h++) {
          uint4 cv = lds128(sb + OFF_MOD2 + ((2 * c + h) * 4 + j) * 16), sv = lds128(sb + OFF_MOD2 + 896 + ((2 * c + h) * 4 + j) * 16);
          uint32_t cw[4] = {cv.x, cv.y, cv.z, cv.w}, sw[4] = {sv.x, sv.y, sv.z, sv.w};
#pragma unroll
          for (int i = 0; i < 8; i++) {
            uint32_t& x = A[4 * c + 2 * h + (i >> 2)][i & 3];
            float2 st = (i & 1) ? st1 : st0;
            x = hfma2(pack2(fmaf(bf_lo(x), st.x, st.y), fmaf(bf_hi(x), st.x, st.y)), cw[i >> 1], sw[i >> 1]);
          }
        }
        if (c < 6) {
          mbar_wait(BAR(B_Z2W + c));
          wg_fence();
          const int p0 = c < 2 ? 16 + 2 * c : (c == 2 ? 15 : 14 + 2 * c);
#pragma unroll
          for (int ks = 0; ks < 4; ks++) wg_rs112<1>(acc, A[4 * c + ks], desc(PG * (p0) + ks * 2048, c == 2 ? 11 * PG : PG), (c | ks) != 0);
        }
      }
      mbar_wait(BAR(B_Z2W + 6));
      wg_fence();
#pragma unroll
      for (int ks = 0; ks < 4; ks++) wg_rs112<1>(acc, A[24 + ks], desc(PG * (0) + ks * 2048, PG), 1);
      wg_commit();
      wg_wait<0>(); keep<56>(acc);
      warp_arrive(BAR(B_Z2PASS), lane);
      STAMP(13);
      {
        float s0 = 0.f, s1 = 0.f;
        const uint32_t stg = PAGE(a ? 7 : 2) + ((lane >> 4) * 8 + (lane & 7)) * 128 + ((((uint32_t)(2 * w) + ((lane >> 3) & 1)) ^ lx) << 4);
#pragma unroll
        for (int t = 0; t < 14; t += 2) {
          uint32_t v[4];
#pragma unroll
          for (int i = 0; i < 4; i++) {
            v[i] = pack2(gelu(acc[4 * t + 2 * i]), gelu(acc[4 * t + 2 * i + 1]));
            acc[4 * t + 2 * i] = bf_lo(v[i]); acc[4 * t + 2 * i + 1] = bf_hi(v[i]);
            if (i & 1) s1 += acc[4 * t + 2 * i] + acc[4 * t + 2 * i + 1]; else s0 += acc[4 * t + 2 * i] + acc[4 * t + 2 * i + 1];
          }
          stsm4t(stg + t * 1024, v[0], v[1], v[2], v[3]);
        }
        fence_async_smem();
        s0 = quad_sum(s0); s1 = quad_sum(s1);
        float m0 = s0 * (1.f / 112.f), m1 = s1 * (1.f / 112.f), q0 = 0.f, q1 = 0.f;
#pragma unroll
        for (int t = 0; t < 14; t++) {
          float d;
          d = acc[4 * t] - m0; q0 = fmaf(d, d, q0); d = acc[4 * t + 1] - m0; q0 = fmaf(d, d, q0);
          d = acc[4 * t + 2] - m1; q1 = fmaf(d, d, q1); d = acc[4 * t + 3] - m1; q1 = fmaf(d, d, q1);
        }
        q0 = quad_sum(q0); q1 = quad_sum(q1);
        const size_t row = 128 * rb + 64 * a + r0;
        if (j == 0) { g_st2[row * 8 + c8] = make_float2(s0, q0); g_st2[(row + 8) * 8 + c8] = make_float2(s1, q1); }
        warp_arrive(BAR(B_STG + a), lane);
      }
      STAMP(14);
#pragma unroll
      for (int c = 0; c < 7; c++) {
        mbar_wait(BAR(B_Z1W + c));
        wg_fence();
        const int p0 = c == 0 ? 4 : c == 1 ? 6 : c == 2 ? 9 : c == 3 ? 11 : c == 4 ? 16 : c == 5 ? 18 : 0;
#pragma unroll
        for (int ks = 0; ks < 4; ks++) wg_rs112<1>(acc, A[4 * c + ks], desc(PG * (p0) + ks * 2048, c == 1 ? 8 * PG : PG), (c | ks) != 0);
        wg_commit();
        if (c == 3) { wg_wait<2>(); warp_arrive(BAR(B_Z1C), lane); }
        if (c == 5) { wg_wait<2>(); warp_arrive(BAR(B_Z1C + 1), lane); }
      }
      wg_wait<1>(); warp_arrive(BAR(B_Z1C + 2), lane);
      wg_wait<0>(); keep<56>(acc);
      asm volatile("barrier.cluster.wait.acquire.aligned;" ::: "memory");
      if (lane == 0) mbar_arrive_remote(mapa(BAR(B_X5FREE), peer));
      STAMP(15);
#pragma unroll
      for (int i = 0; i < 28; i++) z1p[i] = pack2(gelu(acc[2 * i]), gelu(acc[2 * i + 1]));
    }
    STAMP(16);
    {
      float acc[112];
      uint32_t A[2][16];
      float c0 = 0.f, c1 = 0.f;
      const size_t row = 128 * rb + 64 * a + r0;
      const float bs0 = __bfloat162float(P.pbsp[row]), bs1 = __bfloat162float(P.pbsp[row + 8]);
      auto prep = [&](int i, int s, uint32_t* Af) {
        mbar_wait(BAR(B_S5F + i));
        const uint32_t pa = PAGE(s == 0 ? 20 : 6 * s - 4) + a * PG;
#pragma unroll
        for (int ks = 0; ks < 4; ks++) ldsm4(Af + 4 * ks, LDA(pa, ks));
#pragma unroll
        for (int h = 0; h < 2; h++) {
          uint4 rv = lds128(sb + OFF_R5 + i * 128 + j * 32 + h * 16);
          uint32_t rw[4] = {rv.x, rv.y, rv.z, rv.w};
#pragma unroll
          for (int q = 0; q < 2; q++) {
            uint4 mv = lds128(sb + OFF_MU5 + i * 256 + j * 64 + (2 * h + q) * 16);
            uint32_t* p = Af + 4 * (2 * h + q);
            p[0] = hmul2(p[0], rw[2 * q]); p[1] = hmul2(p[1], rw[2 * q]); p[2] = hmul2(p[2], rw[2 * q + 1]); p[3] = hmul2(p[3], rw[2 * q + 1]);
            c0 = fmaf(bf_lo(p[0]), __uint_as_float(mv.x), c0); c0 = fmaf(bf_hi(p[0]), __uint_as_float(mv.y), c0);
            c1 = fmaf(bf_lo(p[1]), __uint_as_float(mv.x), c1); c1 = fmaf(bf_hi(p[1]), __uint_as_float(mv.y), c1);
            c0 = fmaf(bf_lo(p[2]), __uint_as_float(mv.z), c0); c0 = fmaf(bf_hi(p[2]), __uint_as_float(mv.w), c0);
            c1 = fmaf(bf_lo(p[3]), __uint_as_float(mv.z), c1); c1 = fmaf(bf_hi(p[3]), __uint_as_float(mv.w), c1);
          }
        }
      };
      prep(0, 0, A[0]);
      STAMP(17);
#pragma unroll 1
      for (int i0 = 0; i0 < 16; i0 += 4) {
#pragma unroll
        for (int s = 0; s < 4; s++) {
          const int i = i0 + s;
          const uint32_t pb = PG * (s == 0 ? 22 : 6 * s - 2);
          wg_fence();
#pragma unroll
          for (int ks = 0; ks < 4; ks++) wg_rs224<0>(acc, A[s & 1] + 4 * ks, desc(pb + ks * 32, 16), (i | ks) != 0);
          wg_commit();
          wg_wait<1>();
          if (i > 0) warp_arrive(BAR(B_S5E + i - 1), lane);
          if (i < 15) prep(i + 1, (s + 1) & 3, A[(s + 1) & 1]);
        }
      }
      c0 = quad_sum(c0); c1 = quad_sum(c1);
      mbar_wait(BAR(B_X5FREE));
      wg_wait<0>(); keep<112>(acc);
      warp_arrive(BAR(B_S5E + 15), lane);
      STAMP(18);
      const uint32_t xoff = (a ? OFF_XB5_1 : OFF_XB5_0) + t128 * 16;
      const uint32_t rx = mapa(sb + xoff, peer), rbar = mapa(BAR(B_XB5 + a), peer);
#pragma unroll
      for (int q = 0; q < 7; q++) {
        const float* s = acc + 56 + 8 * q;
        st_async4(rx + q * 2048, pack2(s[0] - c0, s[1] - c0), pack2(s[2] - c1, s[3] - c1), pack2(s[4] - c0, s[5] - c0), pack2(s[6] - c1, s[7] - c1), rbar);
      }
      c0 = bs0 - c0; c1 = bs1 - c1;
      __nv_bfloat16* urow = g_u + row * FH + 112 * c8 + 2 * j;
      mbar_wait(BAR(B_XB5 + a));
#pragma unroll
      for (int q = 0; q < 7; q++) {
        uint4 v = lds128(sb + xoff + q * 2048);
        uint32_t vw[4] = {v.x, v.y, v.z, v.w};
#pragma unroll
        for (int i = 0; i < 4; i++) {
          float cc = (i & 1) ? c1 : c0;
          uint32_t z = z1p[4 * q + i];
          uint32_t r = pack2((acc[8 * q + 2 * i] + bf_lo(vw[i]) + cc) * bf_lo(z), (acc[8 * q + 2 * i + 1] + bf_hi(vw[i]) + cc) * bf_hi(z));
          *(uint32_t*)(urow + (i & 1) * 8 * FH + 16 * q + (i >> 1) * 8) = r;
        }
      }
      __syncwarp();
      if (lane == 0) { mbar_arrive_remote(mapa(BAR(B_X6FREE), peer)); if (a == 1) mbar_arrive(BAR(B_XRD)); }
      bar_sync(2 + a, 128);
      if (t128 == 0) publish(C_U + (2 * rb + a) * 2 + (c8 >> 2));
    }
    STAMP(19);
    {
      const size_t off = (size_t)(128 * rb + 64 * a + r0) * DM + 56 * c8 + 2 * j;
      uint32_t xr[14];
#pragma unroll
      for (int t = 0; t < 7; t++) { xr[2 * t] = __ldcg((const uint32_t*)(g_x1 + off + 8 * t)); xr[2 * t + 1] = __ldcg((const uint32_t*)(g_x1 + off + 8 * DM + 8 * t)); }
      uint32_t A[28][4];
      float as[28], ak[28];
#pragma unroll
      for (int c = 0; c < 7; c++) {
        mbar_wait(BAR(B_A6 + 7 * a + c));
        const uint32_t pa = PAGE(16 + 5 * a + (c < 5 ? c : c - 5));
#pragma unroll
        for (int ks = 0; ks < 4; ks++) ldsm4(A[4 * c + ks], LDA(pa, ks));
        if (c < 2) warp_arrive(BAR(B_A6RD + 2 * a + c), lane);
        mbar_wait(BAR(B_B6 + c));
        wg_fence();
#pragma unroll
        for (int ks = 0; ks < 4; ks++) wg_rs56<1>(as, A[4 * c + ks], desc(PG * (2 + 2 * c) + ks * 2048, 0), (c | ks) != 0);
        if (c < 6) {
#pragma unroll
          for (int ks = 0; ks < 4; ks++) wg_rs56<1>(ak, A[4 * c + ks], desc(PG * (3 + 2 * c) + ks * 2048, 0), (c | ks) != 0);
        }
      }
      wg_commit();
#pragma unroll
      for (int ks = 0; ks < 4; ks++) wg_rs56<1>(ak, A[24 + ks], desc(PG * (15) + ks * 2048, 0), 1);
      wg_commit();
      mbar_wait(BAR(B_X6FREE));
      wg_wait<1>(); keep<28>(as);
      const uint32_t xoff = a * PG + t128 * 16;
      const uint32_t rx = mapa(sb + xoff, peer), rbar = mapa(BAR(B_XB6 + a), peer);
#pragma unroll
      for (int q = 0; q < 3; q++) {
        const float* s = as + 8 * q;
        st_async4(rx + q * 2048, pack2(s[0], s[1]), pack2(s[2], s[3]), pack2(s[4], s[5]), pack2(s[6], s[7]), rbar);
      }
      st_async2(rx + 6144 - t128 * 8, pack2(as[24], as[25]), pack2(as[26], as[27]), rbar);
      wg_wait<0>(); keep<28>(ak);
      mbar_wait(BAR(B_XB6 + a));
      uint32_t vw[14];
#pragma unroll
      for (int q = 0; q < 3; q++) { uint4 v = lds128(sb + xoff + q * 2048); vw[4 * q] = v.x; vw[4 * q + 1] = v.y; vw[4 * q + 2] = v.z; vw[4 * q + 3] = v.w; }
      { float2 v = lds64f(sb + a * PG + 6144 + t128 * 8); vw[12] = __float_as_uint(v.x); vw[13] = __float_as_uint(v.y); }
#pragma unroll
      for (int t = 0; t < 7; t++) {
        float2 gb = lds64f(sb + OFF_GB + (8 * t + 2 * j) * 4);
        *(uint32_t*)(P.out + off + 8 * t) =
            pack2(fmaf(gb.x, ak[4 * t] + bf_lo(vw[2 * t]), bf_lo(xr[2 * t])), fmaf(gb.y, ak[4 * t + 1] + bf_hi(vw[2 * t]), bf_hi(xr[2 * t])));
        *(uint32_t*)(P.out + off + 8 * DM + 8 * t) =
            pack2(fmaf(gb.x, ak[4 * t + 2] + bf_lo(vw[2 * t + 1]), bf_lo(xr[2 * t + 1])), fmaf(gb.y, ak[4 * t + 3] + bf_hi(vw[2 * t + 1]), bf_hi(xr[2 * t + 1])));
      }
    }
    if (b == 0 && tid == 0) st_relaxed(&g_epoch, ep);
  }
}

typedef CUresult (*EncodeFn)(CUtensorMap*, CUtensorMapDataType, cuuint32_t, void*, const cuuint64_t*, const cuuint64_t*, const cuuint32_t*,
                             const cuuint32_t*, CUtensorMapInterleave, CUtensorMapSwizzle, CUtensorMapL2promotion, CUtensorMapFloatOOBfill);

void make_map(EncodeFn enc, CUtensorMap* m, const void* ptr, uint64_t inner, uint64_t outer, uint32_t bi, uint32_t bo) {
  cuuint64_t dims[2] = {inner, outer}, strides[1] = {inner * 2};
  cuuint32_t box[2] = {bi, bo}, es[2] = {1, 1};
  enc(m, CU_TENSOR_MAP_DATA_TYPE_BFLOAT16, 2, const_cast<void*>(ptr), dims, strides, box, es, CU_TENSOR_MAP_INTERLEAVE_NONE,
      CU_TENSOR_MAP_SWIZZLE_128B, CU_TENSOR_MAP_L2_PROMOTION_L2_256B, CU_TENSOR_MAP_FLOAT_OOB_FILL_NONE);
}

}

extern "C" void kernel_launch(void* const* d_in, const int* in_sizes, int n_in, void* d_out, int out_size) {
  static EncodeFn enc = nullptr;
  static void *po, *px1, *pu;
  if (!enc) {
    void* fn = nullptr;
    cudaDriverEntryPointQueryResult st;
    cudaGetDriverEntryPoint("cuTensorMapEncodeTiled", &fn, cudaEnableDefault, &st);
    enc = (EncodeFn)fn;
    cudaGetSymbolAddress(&po, g_o);
    cudaGetSymbolAddress(&px1, g_x1);
    cudaGetSymbolAddress(&pu, g_u);
    cudaFuncSetAttribute(fused_kernel, cudaFuncAttributeMaxDynamicSharedMemorySize, SMEM_BYTES);
  }
  typedef const __nv_bfloat16* bp;
  Params P;
  P.px = (bp)d_in[0]; P.pwo = (bp)d_in[2]; P.pwin = (bp)d_in[4]; P.pwsp = (bp)d_in[5]; P.pbsp = (bp)d_in[6];
  P.pwout = (bp)d_in[7]; P.pc = (bp)d_in[8]; P.pwmod = (bp)d_in[9]; P.out = (__nv_bfloat16*)d_out;
  make_map(enc, &P.x, d_in[0], DM, SEQ, 64, 128);
  make_map(enc, &P.wqkv, d_in[1], 3 * DM, DM, 56, 64);
  make_map(enc, &P.wo64, d_in[2], DM, DM, 64, 64);
  make_map(enc, &P.wo48, d_in[2], DM, DM, 48, 64);
  make_map(enc, &P.win64, d_in[4], 2 * FH, DM, 64, 64);
  make_map(enc, &P.win48, d_in[4], 2 * FH, DM, 48, 64);
  make_map(enc, &P.wsp, d_in[5], SEQ, SEQ, 64, 128);
  make_map(enc, &P.wout, d_in[7], DM, FH, 56, 64);
  make_map(enc, &P.o, po, DM, SEQ, 64, 64);
  make_map(enc, &P.x1, px1, DM, SEQ, 64, 64);
  make_map(enc, &P.u, pu, FH, SEQ, 64, 64);
  fused_kernel<<<128, 384, SMEM_BYTES, cudaStreamPerThread>>>(P);
}
```

```cpp
#include <cuda_runtime.h>
#include <cuda_bf16.h>
#include <cuda.h>
#include <stdint.h>

namespace {

constexpr int SEQ = 2048, DM = 448, FH = 896;
constexpr uint32_t PG = 8192;
constexpr uint32_t MISC = 27 * PG;
constexpr uint32_t OFF_BAR = MISC + 3072;
constexpr uint32_t OFF_MOD1 = OFF_BAR + 1408;
constexpr uint32_t OFF_RED = OFF_MOD1 + 1792;
constexpr uint32_t OFF_MOD2 = OFF_RED + 256;
constexpr uint32_t OFF_GA = OFF_MOD2 + 1792;
constexpr uint32_t OFF_GB = OFF_GA + 448;
constexpr uint32_t OFF_R5 = OFF_GB + 224;
constexpr uint32_t SMEM_BYTES = OFF_R5 + 2048;
constexpr uint32_t OFF_XB5_0 = 0;
constexpr uint32_t OFF_XB5_1 = 25 * PG + 5120;
static_assert(SMEM_BYTES <= 232448, "smem");

enum : int {
  B_WK = 0, B_WV, B_WQ, B_WO, B_Z2W  , B_Z1W = B_Z2W + 3  , B_B6 = B_Z1W + 3  , B_X = B_B6 + 3  , B_XFREE = B_X + 2,
  B_A3 = 16  , B_A4 = B_A3 + 7  , B_A6 = B_A4 + 14  , B_ST2 = B_A6 + 14  ,
  B_XB5 = B_ST2 + 2  , B_XB6 = B_XB5 + 2  , B_RAW = B_XB6 + 2  , B_END1 = B_RAW + 2,
  B_CNT2 = 64, B_S5F = B_CNT2  , B_STGDONE = B_S5F + 16, B_MOD2,
  B_CNT4 = 96, B_S3MMA = B_CNT4, B_A4RD  , B_STG = B_A4RD + 2  , B_A6RD = B_STG + 2  , B_KRDY = B_A6RD + 2  ,
  B_A4E = B_KRDY + 4, B_XRD, B_TURN  , B_END4 = B_TURN + 3,
  B_CNT8 = 112, B_KPASS = B_CNT8, B_VPASS, B_QPASS, B_ATT, B_Z2PASS, B_Z2C, B_Z1C  , B_S5E = B_Z1C + 3  , B_X5FREE = B_S5E + 16, B_X6FREE, B_END8,
  B_CNT9 = 144, B_KALL = B_CNT9, B_VALL,
  B_COUNT = 160
};
static_assert(B_XFREE == 15 && B_XB5 >= 48 && B_END1 <= B_CNT2 && B_END4 <= B_CNT8 && B_END8 <= B_CNT9, "barriers");

constexpr int C_K = 0  , C_O = 256, C_X = 288, C_Z = 320, C_U = 352, C_COUNT = 416;

struct Small {
  uint32_t epoch, pad[31];
  uint32_t mod[2688];
  uint32_t cnt[C_COUNT * 8];
  float2 st2[SEQ];
  uint8_t zs[32 * 1024];
  float2 st1[SEQ * 4];
};
__device__ __align__(1024) Small g_s;
#define g_epoch g_s.epoch
#define g_mod g_s.mod
#define g_cnt g_s.cnt
#define g_st1 g_s.st1
#define g_st2 g_s.st2
__device__ __align__(1024) uint8_t g_kv[16 * 8 * 2 * 16384];
__device__ __align__(1024) __nv_bfloat16 g_o[SEQ * DM];
__device__ __align__(1024) __nv_bfloat16 g_x1[SEQ * DM];
__device__ __align__(1024) __nv_bfloat16 g_u[SEQ * FH];
__device__ __align__(1024) uint8_t g_z2t[32 * FH * 128];
#define STAMP(i) do {} while (0)
#define SSTAMP(i) do {} while (0)

struct Params {
  CUtensorMap x, wsp, wqkv, wo64, wo48, win64, win48, wout64, wout48, o, x1, u;
  const __nv_bfloat16 *px, *pwqkv, *pwo, *pwin, *pwsp, *pbsp, *pwout, *pc, *pwmod;
  __nv_bfloat16* out;
};

__device__ __forceinline__ uint32_t smem_u32(const void* p) { return (uint32_t)__cvta_generic_to_shared(p); }
__device__ __forceinline__ void mbar_init(uint32_t bar, uint32_t cnt) { asm volatile("mbarrier.init.shared::cta.b64 [%0], %1;" ::"r"(bar), "r"(cnt)); }
__device__ __forceinline__ void mbar_expect(uint32_t bar, uint32_t bytes) { asm volatile("mbarrier.arrive.expect_tx.shared::cta.b64 _, [%0], %1;" ::"r"(bar), "r"(bytes) : "memory"); }
__device__ __forceinline__ void mbar_arrive(uint32_t bar) { asm volatile("mbarrier.arrive.shared::cta.b64 _, [%0];" ::"r"(bar) : "memory"); }
__device__ __forceinline__ void mbar_arrive_remote(uint32_t rbar) { asm volatile("mbarrier.arrive.shared::cluster.b64 _, [%0];" ::"r"(rbar) : "memory"); }
__device__ __forceinline__ uint32_t mapa(uint32_t addr, uint32_t cta) { uint32_t r; asm volatile("mapa.shared::cluster.u32 %0, %1, %2;" : "=r"(r) : "r"(addr), "r"(cta)); return r; }
__device__ __forceinline__ void mbar_wait2(uint32_t bar, int& bud) {
  asm volatile("{\n.reg .pred p;\nWLOOP:\nmbarrier.try_wait.parity.shared::cta.b64 p, [%1], 0;\n@p bra WDONE;\n"
               "add.s32 %0, %0, -1;\nsetp.gt.s32 p, %0, 0;\n@p bra WLOOP;\nWDONE:\n}" : "+r"(bud) : "r"(bar) : "memory");
}
__device__ __forceinline__ void bar_sync(int id, int n) { asm volatile("bar.sync %0, %1;" ::"r"(id), "r"(n) : "memory"); }
__device__ __forceinline__ void bar_arrive(int id, int n) { asm volatile("bar.arrive %0, %1;" ::"r"(id), "r"(n) : "memory"); }
__device__ __forceinline__ void fence_async_smem() { asm volatile("fence.proxy.async.shared::cta;" ::: "memory"); }
__device__ __forceinline__ void fence_async_glob() { asm volatile("fence.proxy.async.global;" ::: "memory"); }
#define ELECT(body) "{\n.reg .pred p;\nelect.sync _|p, 0xffffffff;\n@p " body "\n}"
__device__ __forceinline__ void e_expect(uint32_t bar, uint32_t bytes) { asm volatile(ELECT("mbarrier.arrive.expect_tx.shared::cta.b64 _, [%0], %1;") ::"r"(bar), "r"(bytes) : "memory"); }
__device__ __forceinline__ void e_arrive(uint32_t bar) { __syncwarp(); asm volatile(ELECT("mbarrier.arrive.shared::cta.b64 _, [%0];") ::"r"(bar) : "memory"); }
__device__ __forceinline__ void e_arrive_remote(uint32_t rbar) { asm volatile(ELECT("mbarrier.arrive.shared::cluster.b64 _, [%0];") ::"r"(rbar) : "memory"); }
__device__ __forceinline__ void e_tma2d(uint32_t dst, const CUtensorMap* map, int c0, int c1, uint32_t bar) {
  asm volatile(ELECT("cp.async.bulk.tensor.2d.shared::cluster.global.mbarrier::complete_tx::bytes [%0], [%1, {%3, %4}], [%2];")
               ::"r"(dst), "l"(map), "r"(bar), "r"(c0), "r"(c1) : "memory");
}
__device__ __forceinline__ void bulk_ld(uint32_t dst, const void* src, uint32_t bytes, uint32_t bar) {
  asm volatile("cp.async.bulk.shared::cluster.global.mbarrier::complete_tx::bytes [%0], [%1], %2, [%3];"
               ::"r"(dst), "l"(src), "r"(bytes), "r"(bar) : "memory");
}
__device__ __forceinline__ void e_bulk_ld(uint32_t dst, const void* src, uint32_t bytes, uint32_t bar) {
  asm volatile(ELECT("cp.async.bulk.shared::cluster.global.mbarrier::complete_tx::bytes [%0], [%1], %2, [%3];")
               ::"r"(dst), "l"(src), "r"(bytes), "r"(bar) : "memory");
}
__device__ __forceinline__ void e_bulk_st(void* dst, uint32_t src, uint32_t bytes) {
  asm volatile(ELECT("cp.async.bulk.global.shared::cta.bulk_group [%0], [%1], %2;") ::"l"(dst), "r"(src), "r"(bytes) : "memory");
}
__device__ __forceinline__ void e_bulk_red_f32(void* dst, uint32_t src, uint32_t bytes) {
  asm volatile(ELECT("cp.reduce.async.bulk.global.shared::cta.bulk_group.add.f32 [%0], [%1], %2;") ::"l"(dst), "r"(src), "r"(bytes) : "memory");
}
__device__ __forceinline__ void e_tma2d_st(const CUtensorMap* map, int c0, int c1, uint32_t src) {
  asm volatile(ELECT("cp.async.bulk.tensor.2d.global.shared::cta.bulk_group [%0, {%2, %3}], [%1];") ::"l"(map), "r"(src), "r"(c0), "r"(c1) : "memory");
}
__device__ __forceinline__ void bulk_done() {
  asm volatile("cp.async.bulk.commit_group;" ::: "memory");
  asm volatile("cp.async.bulk.wait_group 0;" ::: "memory");
  __syncwarp();
}
__device__ __forceinline__ void l2_prefetch(const void* p, int bytes, int lane) {
#pragma unroll 1
  for (int o = lane * 128; o < bytes; o += 4096) asm volatile("prefetch.global.L2 [%0];" ::"l"((const uint8_t*)p + o) : "memory");
}
__device__ __forceinline__ void prefetch_map(const CUtensorMap* m) { asm volatile("prefetch.tensormap [%0];" ::"l"(m) : "memory"); }
__device__ __forceinline__ uint32_t ld_acquire(const uint32_t* p) { uint32_t v; asm volatile("ld.acquire.gpu.global.u32 %0, [%1];" : "=r"(v) : "l"(p) : "memory"); return v; }
__device__ __forceinline__ uint32_t ld_relaxed(const uint32_t* p) { uint32_t v; asm volatile("ld.relaxed.gpu.global.u32 %0, [%1];" : "=r"(v) : "l"(p) : "memory"); return v; }
__device__ __forceinline__ uint4 ld_relaxed4(const uint32_t* p) {
  uint4 v; asm volatile("ld.relaxed.gpu.global.v4.u32 {%0,%1,%2,%3}, [%4];" : "=r"(v.x), "=r"(v.y), "=r"(v.z), "=r"(v.w) : "l"(p) : "memory"); return v;
}
__device__ __forceinline__ void st_relaxed(uint32_t* p, uint32_t v) { asm volatile("st.relaxed.gpu.global.u32 [%0], %1;" ::"l"(p), "r"(v) : "memory"); }
__device__ __forceinline__ void e_release(int c) { __syncwarp(); asm volatile(ELECT("red.release.gpu.global.add.u32 [%0], 1;") ::"l"(&g_cnt[c * 8]) : "memory"); }
__device__ __forceinline__ void e_publish(int c) { bulk_done(); fence_async_glob(); e_release(c); }
__device__ __forceinline__ bool reached(int c, uint32_t target) { return (int)(ld_acquire(&g_cnt[c * 8]) - target) >= 0; }
__device__ __forceinline__ void ldsm4(uint32_t* r, uint32_t addr) {
  asm volatile("ldmatrix.sync.aligned.m8n8.x4.shared.b16 {%0,%1,%2,%3}, [%4];" : "=r"(r[0]), "=r"(r[1]), "=r"(r[2]), "=r"(r[3]) : "r"(addr) : "memory");
}
__device__ __forceinline__ void stsm4(uint32_t addr, uint32_t r0, uint32_t r1, uint32_t r2, uint32_t r3) {
  asm volatile("stmatrix.sync.aligned.m8n8.x4.shared.b16 [%0], {%1,%2,%3,%4};" ::"r"(addr), "r"(r0), "r"(r1), "r"(r2), "r"(r3) : "memory");
}
__device__ __forceinline__ void stsm2(uint32_t addr, uint32_t r0, uint32_t r1) {
  asm volatile("stmatrix.sync.aligned.m8n8.x2.shared.b16 [%0], {%1,%2};" ::"r"(addr), "r"(r0), "r"(r1) : "memory");
}
__device__ __forceinline__ void stsm4t(uint32_t addr, uint32_t r0, uint32_t r1, uint32_t r2, uint32_t r3) {
  asm volatile("stmatrix.sync.aligned.m8n8.x4.trans.shared.b16 [%0], {%1,%2,%3,%4};" ::"r"(addr), "r"(r0), "r"(r1), "r"(r2), "r"(r3) : "memory");
}
__device__ __forceinline__ uint4 lds128(uint32_t addr) {
  uint4 v; asm volatile("ld.shared.v4.u32 {%0,%1,%2,%3}, [%4];" : "=r"(v.x), "=r"(v.y), "=r"(v.z), "=r"(v.w) : "r"(addr) : "memory"); return v;
}
__device__ __forceinline__ float2 lds64f(uint32_t addr) {
  float2 v; asm volatile("ld.shared.v2.f32 {%0,%1}, [%2];" : "=f"(v.x), "=f"(v.y) : "r"(addr) : "memory"); return v;
}
__device__ __forceinline__ void sts16(uint32_t addr, uint32_t v) { asm volatile("st.shared.u16 [%0], %1;" ::"r"(addr), "h"((uint16_t)v) : "memory"); }
__device__ __forceinline__ void sts32(uint32_t addr, uint32_t v) { asm volatile("st.shared.u32 [%0], %1;" ::"r"(addr), "r"(v) : "memory"); }
__device__ __forceinline__ void sts64f(uint32_t addr, float x, float y) { asm volatile("st.shared.v2.f32 [%0], {%1,%2};" ::"r"(addr), "f"(x), "f"(y) : "memory"); }
__device__ __forceinline__ void sts32f(uint32_t addr, float v) { asm volatile("st.shared.f32 [%0], %1;" ::"r"(addr), "f"(v) : "memory"); }
__device__ __forceinline__ float lds32f(uint32_t addr) { float v; asm volatile("ld.shared.f32 %0, [%1];" : "=f"(v) : "r"(addr) : "memory"); return v; }
__device__ __forceinline__ void sts128(uint32_t addr, uint4 v) { asm volatile("st.shared.v4.u32 [%0], {%1,%2,%3,%4};" ::"r"(addr), "r"(v.x), "r"(v.y), "r"(v.z), "r"(v.w) : "memory"); }
__device__ __forceinline__ void st_async4(uint32_t raddr, uint32_t a, uint32_t b, uint32_t c, uint32_t d, uint32_t rbar) {
  asm volatile("st.async.shared::cluster.mbarrier::complete_tx::bytes.v4.b32 [%0], {%1,%2,%3,%4}, [%5];" ::"r"(raddr), "r"(a), "r"(b), "r"(c), "r"(d), "r"(rbar) : "memory");
}
__device__ __forceinline__ void st_async2(uint32_t raddr, uint32_t a, uint32_t b, uint32_t rbar) {
  asm volatile("st.async.shared::cluster.mbarrier::complete_tx::bytes.v2.b32 [%0], {%1,%2}, [%3];" ::"r"(raddr), "r"(a), "r"(b), "r"(rbar) : "memory");
}
__device__ __forceinline__ uint32_t pack2(float lo, float hi) { uint32_t r; asm("cvt.rn.bf16x2.f32 %0, %1, %2;" : "=r"(r) : "f"(hi), "f"(lo)); return r; }
__device__ __forceinline__ float bf_lo(uint32_t w) { return __uint_as_float(w << 16); }
__device__ __forceinline__ float bf_hi(uint32_t w) { return __uint_as_float(w & 0xFFFF0000u); }
__device__ __forceinline__ uint32_t hfma2(uint32_t a, uint32_t b, uint32_t c) { uint32_t r; asm("fma.rn.bf16x2 %0, %1, %2, %3;" : "=r"(r) : "r"(a), "r"(b), "r"(c)); return r; }
__device__ __forceinline__ uint32_t hmul2(uint32_t a, uint32_t b) { uint32_t r; asm("mul.rn.bf16x2 %0, %1, %2;" : "=r"(r) : "r"(a), "r"(b)); return r; }
__device__ __forceinline__ uint32_t hsub2(uint32_t a, uint32_t b) { uint32_t r; asm("sub.rn.bf16x2 %0, %1, %2;" : "=r"(r) : "r"(a), "r"(b)); return r; }
__device__ __forceinline__ float ex2v(float x) { float r; asm volatile("ex2.approx.ftz.f32 %0, %1;" : "=f"(r) : "f"(x)); return r; }
__device__ __forceinline__ void stg128(void* p, uint4 v) { asm volatile("st.global.v4.u32 [%0], {%1,%2,%3,%4};" ::"l"(p), "r"(v.x), "r"(v.y), "r"(v.z), "r"(v.w) : "memory"); }
__device__ __forceinline__ uint32_t hadd2(uint32_t a, uint32_t b) { uint32_t r; asm("add.rn.bf16x2 %0, %1, %2;" : "=r"(r) : "r"(a), "r"(b)); return r; }
__device__ __forceinline__ float ex2(float x) { float r; asm("ex2.approx.ftz.f32 %0, %1;" : "=f"(r) : "f"(x)); return r; }
__device__ __forceinline__ float gelu_h(float y) {
  float u = y * fmaf(8.f * 0.0356774081f, y * y, 2.f * 0.7978845608f), t;
  asm("tanh.approx.f32 %0, %1;" : "=f"(t) : "f"(u));
  return fmaf(y, t, y);
}
__device__ __forceinline__ float quad_sum(float v) { v += __shfl_xor_sync(~0u, v, 1); v += __shfl_xor_sync(~0u, v, 2); return v; }
__device__ __forceinline__ float quad_max(float v) { v = fmaxf(v, __shfl_xor_sync(~0u, v, 1)); v = fmaxf(v, __shfl_xor_sync(~0u, v, 2)); return v; }
__device__ __forceinline__ void rowsum_mma(float* c, const uint32_t* a) {
  asm volatile("mma.sync.aligned.m16n8k16.row.col.f32.bf16.bf16.f32 {%0,%1,%2,%3}, {%4,%5,%6,%7}, {%8,%8}, {%0,%1,%2,%3};"
               : "+f"(c[0]), "+f"(c[1]), "+f"(c[2]), "+f"(c[3]) : "r"(a[0]), "r"(a[1]), "r"(a[2]), "r"(a[3]), "r"(0x3F803F80u));
}
__device__ __forceinline__ void wg_fence() { asm volatile("wgmma.fence.sync.aligned;" ::: "memory"); }
__device__ __forceinline__ void wg_commit() { asm volatile("wgmma.commit_group.sync.aligned;" ::: "memory"); }
template <int N> __device__ __forceinline__ void wg_wait() { asm volatile("wgmma.wait_group.sync.aligned %0;" ::"n"(N) : "memory"); }
constexpr uint32_t SMEM0 = 1024;
__device__ __forceinline__ uint64_t desc(uint32_t rt16, uint32_t off, uint32_t lbo) {
  return (uint64_t)(rt16 + (((SMEM0 + off) >> 4) | ((lbo >> 4) << 16))) | ((uint64_t)0x40000040u << 32);
}
template <int N> __device__ __forceinline__ void keep(float* d) {
#pragma unroll
  for (int i = 0; i < N; i++) asm volatile("" : "+f"(d[i]));
}

template <int TB> __device__ __forceinline__ void wg_rs32(float* d, const uint32_t* a, uint64_t db, int sd) {
  asm volatile("{\n.reg .pred p;\nsetp.ne.b32 p, %21, 0;\n"
    "wgmma.mma_async.sync.aligned.m64n32k16.f32.bf16.bf16 {%0, %1, %2, %3, %4, %5, %6, %7, %8, %9, %10, %11, %12, %13, %14, %15}, {%16, %17, %18, %19}, %20, p, 1, 1, %22;\n}"
    : "+f"(d[0]), "+f"(d[1]), "+f"(d[2]), "+f"(d[3]), "+f"(d[4]), "+f"(d[5]), "+f"(d[6]), "+f"(d[7]), "+f"(d[8]), "+f"(d[9]), "+f"(d[10]), "+f"(d[11]), "+f"(d[12]), "+f"(d[13]), "+f"(d[14]), "+f"(d[15])
    : "r"(a[0]), "r"(a[1]), "r"(a[2]), "r"(a[3]), "l"(db), "r"(sd), "n"(TB));
}
template <int TB> __device__ __forceinline__ void wg_rs56(float* d, const uint32_t* a, uint64_t db, int sd) {
  asm volatile("{\n.reg .pred p;\nsetp.ne.b32 p, %33, 0;\n"
    "wgmma.mma_async.sync.aligned.m64n56k16.f32.bf16.bf16 {%0, %1, %2, %3, %4, %5, %6, %7, %8, %9, %10, %11, %12, %13, %14, %15, %16, %17, %18, %19, %20, %21, %22, %23, %24, %25, %26, %27}, {%28, %29, %30, %31}, %32, p, 1, 1, %34;\n}"
    : "+f"(d[0]), "+f"(d[1]), "+f"(d[2]), "+f"(d[3]), "+f"(d[4]), "+f"(d[5]), "+f"(d[6]), "+f"(d[7]), "+f"(d[8]), "+f"(d[9]), "+f"(d[10]), "+f"(d[11]), "+f"(d[12]), "+f"(d[13]), "+f"(d[14]), "+f"(d[15]), "+f"(d[16]), "+f"(d[17]), "+f"(d[18]), "+f"(d[19]), "+f"(d[20]), "+f"(d[21]), "+f"(d[22]), "+f"(d[23]), "+f"(d[24]), "+f"(d[25]), "+f"(d[26]), "+f"(d[27])
    : "r"(a[0]), "r"(a[1]), "r"(a[2]), "r"(a[3]), "l"(db), "r"(sd), "n"(TB));
}
template <int TB> __device__ __forceinline__ void wg_rs64(float* d, const uint32_t* a, uint64_t db, int sd) {
  asm volatile("{\n.reg .pred p;\nsetp.ne.b32 p, %37, 0;\n"
    "wgmma.mma_async.sync.aligned.m64n64k16.f32.bf16.bf16 {%0, %1, %2, %3, %4, %5, %6, %7, %8, %9, %10, %11, %12, %13, %14, %15, %16, %17, %18, %19, %20, %21, %22, %23, %24, %25, %26, %27, %28, %29, %30, %31}, {%32, %33, %34, %35}, %36, p, 1, 1, %38;\n}"
    : "+f"(d[0]), "+f"(d[1]), "+f"(d[2]), "+f"(d[3]), "+f"(d[4]), "+f"(d[5]), "+f"(d[6]), "+f"(d[7]), "+f"(d[8]), "+f"(d[9]), "+f"(d[10]), "+f"(d[11]), "+f"(d[12]), "+f"(d[13]), "+f"(d[14]), "+f"(d[15]), "+f"(d[16]), "+f"(d[17]), "+f"(d[18]), "+f"(d[19]), "+f"(d[20]), "+f"(d[21]), "+f"(d[22]), "+f"(d[23]), "+f"(d[24]), "+f"(d[25]), "+f"(d[26]), "+f"(d[27]), "+f"(d[28]), "+f"(d[29]), "+f"(d[30]), "+f"(d[31])
    : "r"(a[0]), "r"(a[1]), "r"(a[2]), "r"(a[3]), "l"(db), "r"(sd), "n"(TB));
}
template <int TB> __device__ __forceinline__ void wg_rs112(float* d, const uint32_t* a, uint64_t db, int sd) {
  asm volatile("{\n.reg .pred p;\nsetp.ne.b32 p, %61, 0;\n"
    "wgmma.mma_async.sync.aligned.m64n112k16.f32.bf16.bf16 {%0, %1, %2, %3, %4, %5, %6, %7, %8, %9, %10, %11, %12, %13, %14, %15, %16, %17, %18, %19, %20, %21, %22, %23, %24, %25, %26, %27, %28, %29, %30, %31, %32, %33, %34, %35, %36, %37, %38, %39, %40, %41, %42, %43, %44, %45, %46, %47, %48, %49, %50, %51, %52, %53, %54, %55}, {%56, %57, %58, %59}, %60, p, 1, 1, %62;\n}"
    : "+f"(d[0]), "+f"(d[1]), "+f"(d[2]), "+f"(d[3]), "+f"(d[4]), "+f"(d[5]), "+f"(d[6]), "+f"(d[7]), "+f"(d[8]), "+f"(d[9]), "+f"(d[10]), "+f"(d[11]), "+f"(d[12]), "+f"(d[13]), "+f"(d[14]), "+f"(d[15]), "+f"(d[16]), "+f"(d[17]), "+f"(d[18]), "+f"(d[19]), "+f"(d[20]), "+f"(d[21]), "+f"(d[22]), "+f"(d[23]), "+f"(d[24]), "+f"(d[25]), "+f"(d[26]), "+f"(d[27]), "+f"(d[28]), "+f"(d[29]), "+f"(d[30]), "+f"(d[31]), "+f"(d[32]), "+f"(d[33]), "+f"(d[34]), "+f"(d[35]), "+f"(d[36]), "+f"(d[37]), "+f"(d[38]), "+f"(d[39]), "+f"(d[40]), "+f"(d[41]), "+f"(d[42]), "+f"(d[43]), "+f"(d[44]), "+f"(d[45]), "+f"(d[46]), "+f"(d[47]), "+f"(d[48]), "+f"(d[49]), "+f"(d[50]), "+f"(d[51]), "+f"(d[52]), "+f"(d[53]), "+f"(d[54]), "+f"(d[55])
    : "r"(a[0]), "r"(a[1]), "r"(a[2]), "r"(a[3]), "l"(db), "r"(sd), "n"(TB));
}
template <int TB> __device__ __forceinline__ void wg_rs192(float* d, const uint32_t* a, uint64_t db, int sd) {
  asm volatile("{\n.reg .pred p;\nsetp.ne.b32 p, %101, 0;\n"
    "wgmma.mma_async.sync.aligned.m64n192k16.f32.bf16.bf16 {%0, %1, %2, %3, %4, %5, %6, %7, %8, %9, %10, %11, %12, %13, %14, %15, %16, %17, %18, %19, %20, %21, %22, %23, %24, %25, %26, %27, %28, %29, %30, %31, %32, %33, %34, %35, %36, %37, %38, %39, %40, %41, %42, %43, %44, %45, %46, %47, %48, %49, %50, %51, %52, %53, %54, %55, %56, %57, %58, %59, %60, %61, %62, %63, %64, %65, %66, %67, %68, %69, %70, %71, %72, %73, %74, %75, %76, %77, %78, %79, %80, %81, %82, %83, %84, %85, %86, %87, %88, %89, %90, %91, %92, %93, %94, %95}, {%96, %97, %98, %99}, %100, p, 1, 1, %102;\n}"
    : "+f"(d[0]), "+f"(d[1]), "+f"(d[2]), "+f"(d[3]), "+f"(d[4]), "+f"(d[5]), "+f"(d[6]), "+f"(d[7]), "+f"(d[8]), "+f"(d[9]), "+f"(d[10]), "+f"(d[11]), "+f"(d[12]), "+f"(d[13]), "+f"(d[14]), "+f"(d[15]), "+f"(d[16]), "+f"(d[17]), "+f"(d[18]), "+f"(d[19]), "+f"(d[20]), "+f"(d[21]), "+f"(d[22]), "+f"(d[23]), "+f"(d[24]), "+f"(d[25]), "+f"(d[26]), "+f"(d[27]), "+f"(d[28]), "+f"(d[29]), "+f"(d[30]), "+f"(d[31]), "+f"(d[32]), "+f"(d[33]), "+f"(d[34]), "+f"(d[35]), "+f"(d[36]), "+f"(d[37]), "+f"(d[38]), "+f"(d[39]), "+f"(d[40]), "+f"(d[41]), "+f"(d[42]), "+f"(d[43]), "+f"(d[44]), "+f"(d[45]), "+f"(d[46]), "+f"(d[47]), "+f"(d[48]), "+f"(d[49]), "+f"(d[50]), "+f"(d[51]), "+f"(d[52]), "+f"(d[53]), "+f"(d[54]), "+f"(d[55]), "+f"(d[56]), "+f"(d[57]), "+f"(d[58]), "+f"(d[59]), "+f"(d[60]), "+f"(d[61]), "+f"(d[62]), "+f"(d[63]), "+f"(d[64]), "+f"(d[65]), "+f"(d[66]), "+f"(d[67]), "+f"(d[68]), "+f"(d[69]), "+f"(d[70]), "+f"(d[71]), "+f"(d[72]), "+f"(d[73]), "+f"(d[74]), "+f"(d[75]), "+f"(d[76]), "+f"(d[77]), "+f"(d[78]), "+f"(d[79]), "+f"(d[80]), "+f"(d[81]), "+f"(d[82]), "+f"(d[83]), "+f"(d[84]), "+f"(d[85]), "+f"(d[86]), "+f"(d[87]), "+f"(d[88]), "+f"(d[89]), "+f"(d[90]), "+f"(d[91]), "+f"(d[92]), "+f"(d[93]), "+f"(d[94]), "+f"(d[95])
    : "r"(a[0]), "r"(a[1]), "r"(a[2]), "r"(a[3]), "l"(db), "r"(sd), "n"(TB));
}
template <int TB> __device__ __forceinline__ void wg_rs232(float* d, const uint32_t* a, uint64_t db, int sd) {
  asm volatile("{\n.reg .pred p;\nsetp.ne.b32 p, %121, 0;\n"
    "wgmma.mma_async.sync.aligned.m64n232k16.f32.bf16.bf16 {%0, %1, %2, %3, %4, %5, %6, %7, %8, %9, %10, %11, %12, %13, %14, %15, %16, %17, %18, %19, %20, %21, %22, %23, %24, %25, %26, %27, %28, %29, %30, %31, %32, %33, %34, %35, %36, %37, %38, %39, %40, %41, %42, %43, %44, %45, %46, %47, %48, %49, %50, %51, %52, %53, %54, %55, %56, %57, %58, %59, %60, %61, %62, %63, %64, %65, %66, %67, %68, %69, %70, %71, %72, %73, %74, %75, %76, %77, %78, %79, %80, %81, %82, %83, %84, %85, %86, %87, %88, %89, %90, %91, %92, %93, %94, %95, %96, %97, %98, %99, %100, %101, %102, %103, %104, %105, %106, %107, %108, %109, %110, %111, %112, %113, %114, %115}, {%116, %117, %118, %119}, %120, p, 1, 1, %122;\n}"
    : "+f"(d[0]), "+f"(d[1]), "+f"(d[2]), "+f"(d[3]), "+f"(d[4]), "+f"(d[5]), "+f"(d[6]), "+f"(d[7]), "+f"(d[8]), "+f"(d[9]), "+f"(d[10]), "+f"(d[11]), "+f"(d[12]), "+f"(d[13]), "+f"(d[14]), "+f"(d[15]), "+f"(d[16]), "+f"(d[17]), "+f"(d[18]), "+f"(d[19]), "+f"(d[20]), "+f"(d[21]), "+f"(d[22]), "+f"(d[23]), "+f"(d[24]), "+f"(d[25]), "+f"(d[26]), "+f"(d[27]), "+f"(d[28]), "+f"(d[29]), "+f"(d[30]), "+f"(d[31]), "+f"(d[32]), "+f"(d[33]), "+f"(d[34]), "+f"(d[35]), "+f"(d[36]), "+f"(d[37]), "+f"(d[38]), "+f"(d[39]), "+f"(d[40]), "+f"(d[41]), "+f"(d[42]), "+f"(d[43]), "+f"(d[44]), "+f"(d[45]), "+f"(d[46]), "+f"(d[47]), "+f"(d[48]), "+f"(d[49]), "+f"(d[50]), "+f"(d[51]), "+f"(d[52]), "+f"(d[53]), "+f"(d[54]), "+f"(d[55]), "+f"(d[56]), "+f"(d[57]), "+f"(d[58]), "+f"(d[59]), "+f"(d[60]), "+f"(d[61]), "+f"(d[62]), "+f"(d[63]), "+f"(d[64]), "+f"(d[65]), "+f"(d[66]), "+f"(d[67]), "+f"(d[68]), "+f"(d[69]), "+f"(d[70]), "+f"(d[71]), "+f"(d[72]), "+f"(d[73]), "+f"(d[74]), "+f"(d[75]), "+f"(d[76]), "+f"(d[77]), "+f"(d[78]), "+f"(d[79]), "+f"(d[80]), "+f"(d[81]), "+f"(d[82]), "+f"(d[83]), "+f"(d[84]), "+f"(d[85]), "+f"(d[86]), "+f"(d[87]), "+f"(d[88]), "+f"(d[89]), "+f"(d[90]), "+f"(d[91]), "+f"(d[92]), "+f"(d[93]), "+f"(d[94]), "+f"(d[95]), "+f"(d[96]), "+f"(d[97]), "+f"(d[98]), "+f"(d[99]), "+f"(d[100]), "+f"(d[101]), "+f"(d[102]), "+f"(d[103]), "+f"(d[104]), "+f"(d[105]), "+f"(d[106]), "+f"(d[107]), "+f"(d[108]), "+f"(d[109]), "+f"(d[110]), "+f"(d[111]), "+f"(d[112]), "+f"(d[113]), "+f"(d[114]), "+f"(d[115])
    : "r"(a[0]), "r"(a[1]), "r"(a[2]), "r"(a[3]), "l"(db), "r"(sd), "n"(TB));
}
template <int TB> __device__ __forceinline__ void wg_ss112(float* d, uint64_t da, uint64_t db, int sd) {
  asm volatile("{\n.reg .pred p;\nsetp.ne.b32 p, %58, 0;\n"
    "wgmma.mma_async.sync.aligned.m64n112k16.f32.bf16.bf16 {%0, %1, %2, %3, %4, %5, %6, %7, %8, %9, %10, %11, %12, %13, %14, %15, %16, %17, %18, %19, %20, %21, %22, %23, %24, %25, %26, %27, %28, %29, %30, %31, %32, %33, %34, %35, %36, %37, %38, %39, %40, %41, %42, %43, %44, %45, %46, %47, %48, %49, %50, %51, %52, %53, %54, %55}, %56, %57, p, 1, 1, 0, %59;\n}"
    : "+f"(d[0]), "+f"(d[1]), "+f"(d[2]), "+f"(d[3]), "+f"(d[4]), "+f"(d[5]), "+f"(d[6]), "+f"(d[7]), "+f"(d[8]), "+f"(d[9]), "+f"(d[10]), "+f"(d[11]), "+f"(d[12]), "+f"(d[13]), "+f"(d[14]), "+f"(d[15]), "+f"(d[16]), "+f"(d[17]), "+f"(d[18]), "+f"(d[19]), "+f"(d[20]), "+f"(d[21]), "+f"(d[22]), "+f"(d[23]), "+f"(d[24]), "+f"(d[25]), "+f"(d[26]), "+f"(d[27]), "+f"(d[28]), "+f"(d[29]), "+f"(d[30]), "+f"(d[31]), "+f"(d[32]), "+f"(d[33]), "+f"(d[34]), "+f"(d[35]), "+f"(d[36]), "+f"(d[37]), "+f"(d[38]), "+f"(d[39]), "+f"(d[40]), "+f"(d[41]), "+f"(d[42]), "+f"(d[43]), "+f"(d[44]), "+f"(d[45]), "+f"(d[46]), "+f"(d[47]), "+f"(d[48]), "+f"(d[49]), "+f"(d[50]), "+f"(d[51]), "+f"(d[52]), "+f"(d[53]), "+f"(d[54]), "+f"(d[55])
    : "l"(da), "l"(db), "r"(sd), "n"(TB));
}

__device__ __forceinline__ int perm448(int k) { return (k >> 5) * 32 + ((k & 7) >> 1) * 8 + ((k >> 4) & 1) * 4 + ((k >> 3) & 1) * 2 + (k & 1); }
__device__ __forceinline__ int perm64(int k) { return ((k & 7) >> 1) * 16 + (k >> 4) * 4 + ((k >> 3) & 1) * 2 + (k & 1); }

__device__ __forceinline__ float rcp(float x) { float r; asm("rcp.approx.ftz.f32 %0, %1;" : "=f"(r) : "f"(x)); return r; }
__device__ __forceinline__ float silu_bf(float c) { return bf_lo(pack2(c * rcp(1.f + ex2(-1.4426950408889634f * c)), 0.f)); }
__device__ __forceinline__ void fma8(float* acc, uint4 w, float s) {
  acc[0] = fmaf(bf_lo(w.x), s, acc[0]); acc[1] = fmaf(bf_hi(w.x), s, acc[1]);
  acc[2] = fmaf(bf_lo(w.y), s, acc[2]); acc[3] = fmaf(bf_hi(w.y), s, acc[3]);
  acc[4] = fmaf(bf_lo(w.z), s, acc[4]); acc[5] = fmaf(bf_hi(w.z), s, acc[5]);
  acc[6] = fmaf(bf_lo(w.w), s, acc[6]); acc[7] = fmaf(bf_hi(w.w), s, acc[7]);
}
__device__ __forceinline__ float warp_red8(float* v, int lane) {
  bool b4 = lane & 16, b3 = lane & 8, b2 = lane & 4;
  float t[4];
#pragma unroll
  for (int i = 0; i < 4; i++) { float keepv = b4 ? v[i + 4] : v[i], send = b4 ? v[i] : v[i + 4]; t[i] = keepv + __shfl_xor_sync(~0u, send, 16); }
  float u[2];
#pragma unroll
  for (int i = 0; i < 2; i++) { float keepv = b3 ? t[i + 2] : t[i], send = b3 ? t[i] : t[i + 2]; u[i] = keepv + __shfl_xor_sync(~0u, send, 8); }
  float keepv = b2 ? u[1] : u[0], send = b2 ? u[0] : u[1];
  float r = keepv + __shfl_xor_sync(~0u, send, 4);
  r += __shfl_xor_sync(~0u, r, 2);
  r += __shfl_xor_sync(~0u, r, 1);
  return r;
}

template <int NT> __device__ __forceinline__ void stage_rows(const uint32_t* w, uint32_t stg, int lane) {
  const uint32_t sa = stg + (lane & 15) * (NT * 16) + (lane >> 4) * 16;
#pragma unroll
  for (int t = 0; t + 1 < NT; t += 2) stsm4(sa + t * 16, w[2 * t], w[2 * t + 1], w[2 * t + 2], w[2 * t + 3]);
  if (NT & 1) stsm2(sa + (NT - 1) * 16, w[2 * NT - 2], w[2 * NT - 1]);
}
template <int NT> __device__ __forceinline__ void store_rows(const uint32_t* w, uint32_t stg, __nv_bfloat16* gp, int pitch, int lane) {
  stage_rows<NT>(w, stg, lane);
  __syncwarp();
#pragma unroll
  for (int k = 0; k < (NT + 1) / 2; k++) {
    const int i = lane + 32 * k, r = i / NT;
    if (i < 16 * NT) stg128(gp + r * (pitch - 8 * NT) + i * 8, lds128(stg + i * 16));
  }
}
__device__ __forceinline__ uint32_t mod_bad(uint4 v, uint32_t tag) { return (v.x ^ tag) | (v.y ^ tag) | (v.z ^ tag) | (v.w ^ tag); }
__device__ __forceinline__ void put_mod4(uint32_t base, int i, uint4 v, uint32_t s2) {
  const bool isc = i >= 112;
  const float one = isc ? 1.f : 0.f;
  const int k = (isc ? i - 112 : i) * 4;
  base += (isc ? 0 : 896) + perm448(k) * 2;
  sts32(base, hmul2(pack2(bf_lo(v.x) + one, bf_lo(v.y) + one), s2));
  sts32(base + 16, hmul2(pack2(bf_lo(v.z) + one, bf_lo(v.w) + one), s2));
}

__device__ __forceinline__ void tile_stats(const uint32_t* v, float2& st0, float2& st1) {
  float s[2][4] = {};
#pragma unroll
  for (int i = 0; i < 7; i++) rowsum_mma(s[i & 1], v + 4 * i);
  st0.x = s[0][0] + s[1][0]; st1.x = s[0][2] + s[1][2];
  const float m0 = st0.x * (1.f / 112.f), m1 = st1.x * (1.f / 112.f);
  const uint32_t mp0 = pack2(m0, m0), mp1 = pack2(m1, m1);
  float q[2][4] = {};
#pragma unroll
  for (int i = 0; i < 7; i++) {
    uint32_t d[4];
#pragma unroll
    for (int e = 0; e < 4; e++) { d[e] = hsub2(v[4 * i + e], (e & 1) ? mp1 : mp0); d[e] = hmul2(d[e], d[e]); }
    rowsum_mma(q[i & 1], d);
  }
  const float e0 = m0 - bf_lo(mp0), e1 = m1 - bf_lo(mp1);
  st0.y = q[0][0] + q[1][0] - 112.f * e0 * e0; st1.y = q[0][2] + q[1][2] - 112.f * e1 * e1;
}

__host__ __device__ constexpr uint32_t bar_count(int i) { return i >= B_CNT9 ? 9 : i >= B_CNT8 ? 8 : i >= B_CNT4 ? 4 : i >= B_CNT2 ? 2 : 1; }
constexpr uint32_t WE(int wait, int p0, int p1, int full, int c, int type, int add, int n) {
  return (uint32_t)wait | p0 << 8 | p1 << 13 | full << 18 | c << 22 | type << 25 | add << 27 | (uint32_t)n << 29;
}
__constant__ uint32_t c_wprog[49] = {
  WE(B_X, 14, 0, B_WK, 0, 0, 1, 7), WE(0, 15, 0, B_WK, 1, 0, 1, 0), WE(0, 16, 0, B_WK, 2, 0, 1, 0), WE(0, 17, 0, B_WK, 3, 0, 1, 0),
  WE(0, 18, 0, B_WK, 4, 0, 1, 0), WE(0, 19, 0, B_WK, 5, 0, 1, 0), WE(0, 20, 0, B_WK, 6, 0, 1, 0),
  WE(0, 21, 0, B_WV, 0, 0, 2, 7), WE(0, 22, 0, B_WV, 1, 0, 2, 0), WE(0, 23, 0, B_WV, 2, 0, 2, 0), WE(0, 24, 0, B_WV, 3, 0, 2, 0),
  WE(0, 25, 0, B_WV, 4, 0, 2, 0), WE(0, 26, 0, B_WV, 5, 0, 2, 0), WE(B_XFREE, 7, 0, B_WV, 6, 0, 2, 0),
  WE(0, 0, 0, B_WQ, 0, 0, 0, 7), WE(0, 1, 0, B_WQ, 1, 0, 0, 0), WE(0, 2, 0, B_WQ, 2, 0, 0, 0), WE(0, 3, 0, B_WQ, 3, 0, 0, 0),
  WE(0, 4, 0, B_WQ, 4, 0, 0, 0), WE(0, 5, 0, B_WQ, 5, 0, 0, 0), WE(0, 6, 0, B_WQ, 6, 0, 0, 0),
  WE(B_VALL, 20, 21, B_WO, 4, 1, 0, 7), WE(0, 22, 23, B_WO, 5, 1, 0, 0), WE(0, 24, 25, B_WO, 6, 1, 0, 0),
  WE(B_QPASS, 0, 1, B_WO, 0, 1, 0, 0), WE(0, 2, 3, B_WO, 1, 1, 0, 0), WE(0, 4, 5, B_WO, 2, 1, 0, 0), WE(0, 6, 7, B_WO, 3, 1, 0, 0),
  WE(B_A3 + 6, 16, 17, B_Z2W, 0, 2, 2, 3), WE(0, 18, 19, B_Z2W, 1, 2, 2, 0), WE(0, 15, 26, B_Z2W, 2, 2, 2, 0),
  WE(B_S3MMA, 20, 21, B_Z2W + 1, 3, 2, 2, 3), WE(0, 22, 23, B_Z2W + 1, 4, 2, 2, 0), WE(0, 24, 25, B_Z2W + 1, 5, 2, 2, 0),
  WE(B_A4E, 0, 1, B_Z2W + 2, 6, 2, 2, 1),
  WE(B_A4RD, 4, 5, B_Z1W, 0, 2, 0, 2), WE(0, 6, 14, B_Z1W, 1, 2, 0, 0),
  WE(B_A4RD + 1, 9, 10, B_Z1W + 1, 2, 2, 0, 2), WE(0, 11, 12, B_Z1W + 1, 3, 2, 0, 0),
  WE(B_Z2C, 16, 17, B_Z1W + 2, 4, 2, 0, 3), WE(0, 18, 19, B_Z1W + 2, 5, 2, 0, 0), WE(B_Z2PASS, 0, 1, B_Z1W + 2, 6, 2, 0, 0),
  WE(B_S5E + 13, 2, 3, B_B6, 0, 3, 0, 3), WE(0, 4, 5, B_B6, 1, 3, 0, 0), WE(0, 6, 7, B_B6, 2, 3, 0, 0),
  WE(B_S5E + 14, 8, 9, B_B6 + 1, 3, 3, 0, 3), WE(0, 10, 11, B_B6 + 1, 4, 3, 0, 0), WE(0, 12, 13, B_B6 + 1, 5, 3, 0, 0),
  WE(B_S5E + 15, 14, 15, B_B6 + 2, 6, 3, 0, 1)};

__global__ void __cluster_dims__(2, 1, 1) __launch_bounds__(384, 1) fused_kernel(const __grid_constant__ Params P) {
  extern __shared__ __align__(1024) uint8_t smem_raw[];
  const uint32_t sb = smem_u32(smem_raw);
  const int tid = threadIdx.x, lane = tid & 31, warp = __shfl_sync(~0u, tid >> 5, 0);
  const int b = blockIdx.x, rb = b >> 3, c8 = b & 7, cb4 = c8 >> 1, kh = c8 & 1;
  const int h3 = 2 * rb + (cb4 & 1), c4 = 2 * (cb4 >> 1) + kh;
  int bud = 1 << 20;
  auto BAR = [&](int i) { return sb + OFF_BAR + 8u * i; };
  auto PAGE = [&](int i) { return sb + PG * i; };
  auto mbar_wait = [&](uint32_t bar) { mbar_wait2(bar, bud); };
  auto poll = [&](int c, uint32_t target) { while (!__all_sync(~0u, reached(c, target)) && --bud > 0) {} fence_async_glob(); };

  STAMP(0);
  if ((sb & 0xFFFFFFu) != SMEM0) bud = 0;
  uint32_t ep = 0;
  auto cluster_arrive = [&]() { asm volatile("barrier.cluster.arrive.relaxed.aligned;" ::: "memory"); };

  if (warp >= 8) {
    asm volatile("setmaxnreg.dec.sync.aligned.u32 40;");
    auto rows = [&](const CUtensorMap* m, int n, int page, int col, int hh, int bar) {
#pragma unroll 1
      for (int c = 0; c < n; c++) { e_expect(BAR(bar + c), 8192); e_tma2d(PAGE(page + c), m, col + 64 * c, 64 * hh, BAR(bar + c)); }
    };
    const int t96 = tid - 288;
    float sl[5];
    auto unit_load = [&](int u, uint4* w) {
#pragma unroll
      for (int q = 0; q < 5; q++) w[q] = __ldg((const uint4*)(P.pwmod + (size_t)min(t96 + 96 * q, 447) * 2688) + u);
    };
    auto unit_finish = [&](int u, const uint4* w) {
      float acc[8] = {0, 0, 0, 0, 0, 0, 0, 0};
#pragma unroll
      for (int q = 0; q < 5; q++) fma8(acc, w[q], sl[q]);
      const float r = warp_red8(acc, lane);
      const uint32_t red = sb + OFF_RED + (u >= 240 ? 128 : 0);
      if ((lane & 3) == 0) sts32f(red + (warp - 9) * 32 + lane, r);
      bar_sync(9, 96);
      if (t96 < 8) st_relaxed(&g_mod[u * 8 + t96], (pack2(lds32f(red + t96 * 4) + lds32f(red + 32 + t96 * 4) + lds32f(red + 64 + t96 * 4), 0.f) & 0xFFFFu) | (ep << 16));
    };
    auto late_units = [&]() {
#pragma unroll 1
      for (int u = 112 + b; u < 336; u += 128) { uint4 w[5]; unit_load(u, w); unit_finish(u, w); }
    };
    if (warp > 8) {
      uint4 w[5]; uint16_t cc[5];
      unit_load(min(b, 111), w);
#pragma unroll
      for (int q = 0; q < 5; q++) cc[q] = t96 + 96 * q < 448 ? __ldg((const uint16_t*)P.pc + t96 + 96 * q) : (uint16_t)0;
      ep = ld_relaxed(&g_epoch) + 1;
      if (warp == 11) l2_prefetch((const uint8_t*)P.pwqkv + b * 9408, 9408, lane);
      if (warp == 9 && lane < 12) prefetch_map(&P.x + lane);
#pragma unroll 1
      for (int blk = warp - 8; blk < B_COUNT / 16; blk += 3) {
        if (lane == 0) {
          const uint32_t cnt = bar_count(16 * blk);
#pragma unroll
          for (int i = 0; i < 16; i++) mbar_init(BAR(16 * blk + i), cnt);
          asm volatile("fence.mbarrier_init.release.cluster;" ::: "memory");
        }
        __syncwarp();
        if (blk == 3) {
#pragma unroll
          for (int i = 0; i < 6; i++) e_expect(BAR(B_XB5 + i), i < 2 ? 14336 : i < 4 ? 7168 : 4096);
        }
      }
      bar_arrive(7, 352); bar_arrive(8, 128);
      cluster_arrive();
#pragma unroll
      for (int q = 0; q < 5; q++) sl[q] = silu_bf(bf_lo(cc[q]));
      unit_finish(min(b, 111), w);
      SSTAMP(36);
      bar_sync(10, 128);
    }
    if (warp == 8) {
      if (lane == 0) { mbar_init(BAR(B_X), 1); mbar_init(BAR(B_X + 1), 1); }
      __syncwarp();
      e_expect(BAR(B_X), 16384); e_expect(BAR(B_X + 1), 6 * 16384);
#pragma unroll
      for (int c = 0; c < 7; c++) e_tma2d(PAGE(2 * c), &P.x, 64 * c, 128 * rb, BAR(B_X + (c > 0)));
      if (lane == 0) {
#pragma unroll
        for (int i = 0; i < B_X; i++) mbar_init(BAR(i), 1);
        mbar_init(BAR(B_XFREE), 8);
      }
      __syncwarp();
      bar_arrive(6, 288); bar_arrive(10, 128);
      cluster_arrive();
#pragma unroll 1
      for (int i = 0; i < 49; i++) {
        if (i == 21) bar_sync(8, 128);
        if (i == 42) {
#pragma unroll 1
          for (int k = 0; k < 16; k++) {
            const int s = k & 3;
            if (k == 1) mbar_wait(BAR(B_STGDONE));
            if (k) mbar_wait(BAR(k >= 4 ? B_S5E + k - 4 : B_Z1C + k - 1));
            e_expect(BAR(B_S5F + k), 16384);
            e_tma2d(PAGE(s == 0 ? 20 : 6 * s - 4), &P.wsp, 1024 * kh + 64 * (k < 8 ? 2 * k : 2 * k - 15), 128 * rb, BAR(B_S5F + k));
          }
        }
        const uint32_t e = c_wprog[i], type = (e >> 25) & 3;
        if (e & 255) mbar_wait(BAR(e & 255));
        const uint32_t bar = BAR((e >> 18) & 15);
        const int col = (type == 0 ? (56 * c8 & ~15) : 112 * (type == 1 ? c4 : type == 2 ? c8 : cb4)) + 448 * ((e >> 27) & 3);
        const int row = 64 * ((e >> 22) & 7) + (type == 3 ? 448 * kh : 0);
        const CUtensorMap* m = &P.wqkv + (type == 0 ? 0 : 2 * type - 1);
        if (e >> 29) e_expect(bar, (e >> 29) * (type ? 14336 : 8192));
        e_tma2d(PAGE((e >> 8) & 31), m, col, row, bar);
        if (type) e_tma2d(PAGE((e >> 13) & 31), m + 1, col + 64, row, bar);
        if (i == 0) SSTAMP(44);
        if (i == 7) SSTAMP(45);
        if (i == 12) SSTAMP(46);
        if (i == 14) SSTAMP(47);
        if (i == 20) SSTAMP(48);
        if (i == 21) SSTAMP(49);
        if (i == 27) SSTAMP(50);
      }
    } else if (warp == 9) {
#pragma unroll 1
      for (int kv = 0; kv < 2; kv++) {
        const uint32_t dst = PAGE(8 + 6 * kv), bar = BAR(B_KALL + kv);
        mbar_wait(BAR(kv ? B_KPASS : B_XFREE));
        if (rb < 2) {
#pragma unroll 1
          for (int i = lane; i < (2 - rb) * 1024; i += 32) sts128(dst + i * 16, make_uint4(0, 0, 0, 0));
          fence_async_smem();
          __syncwarp();
        }
        e_expect(bar, min(rb, 2) * 16384);
        uint32_t todo = rb >= 2 ? 3 : rb;
        while (todo) {
          const uint32_t m = __ballot_sync(~0u, reached(C_K + 128 * kv + max(b - 8 - 8 * (lane & 1), 0), 2 * ep) || --bud <= 0) & todo;
          if (m) fence_async_glob();
#pragma unroll
          for (int d = 0; d < 2; d++)
            if ((m >> d) & 1) { e_bulk_ld(dst + (1 - d) * 16384, g_kv + (size_t)((b - 8 - 8 * d) * 2 + kv) * 16384, 16384, bar); SSTAMP(2 * kv + d); }
          todo &= ~m;
        }
      }
      late_units();
      mbar_wait(BAR(B_ATT));
      poll(C_O + h3, 32 * ep);
      SSTAMP(4);
      rows(&P.o, 7, 8, 0, h3, B_A3);
      mbar_wait(BAR(B_Z2PASS));
      const int hme = 16 * kh + ((lane & 8) ? 2 * (lane & 15) - 15 : 2 * (lane & 15));
      bool rdy = lane >= 16;
#pragma unroll 1
      for (int i = 0; i < 16; i++) {
        const int s = i & 3, h = 16 * kh + (i < 8 ? 2 * i : 2 * i - 15);
        if (i == 1) mbar_wait(BAR(B_STGDONE));
        if (i) mbar_wait(BAR(i >= 4 ? B_S5E + i - 4 : B_Z1C + i - 1));
        while ((~__ballot_sync(~0u, rdy) & (i < 4 ? 0xFFu : ~0u)) != 0) {
          if (!rdy && (reached(C_Z + hme, 8 * ep) || --bud <= 0)) {
            rdy = true;
            fence_async_glob();
            bulk_ld(PAGE(26) + lane * 512, g_st2 + hme * 64, 512, BAR(B_RAW + (lane >> 3)));
          }
        }
        if ((i & 3) == 0 && i < 8) fence_async_glob();
        const uint32_t dst = PAGE(s == 0 ? 22 : 6 * s - 2);
        const uint8_t* src = g_z2t + (size_t)h * FH * 128;
        e_expect(BAR(B_S5F + i), 29696);
        e_bulk_ld(dst + 28672, g_s.zs + h * 1024, 1024, BAR(B_S5F + i));
        e_bulk_ld(dst, src + 14336 * c8, 14336, BAR(B_S5F + i));
        e_bulk_ld(dst + 14336, src + 14336 * (c8 ^ 1), 14336, BAR(B_S5F + i));
        if (i == 0) SSTAMP(7);
      }
    } else {
      const int a = warp - 10, hh = 2 * rb + a;
      mbar_wait(BAR(B_X + 1));
      if (a) {
        l2_prefetch((const uint8_t*)P.pwo + b * 3136, 3136, lane);
        l2_prefetch((const uint8_t*)P.pwin + b * 12544, 12544, lane);
      } else if (b < 112) {
#pragma unroll 1
        for (int i = 0; i < 4; i++) l2_prefetch(P.pwmod + (size_t)(4 * b + i) * 2688 + 896, 3584, lane);
      }
#pragma unroll 1
      for (int kv = 0; kv < 2; kv++) {
        mbar_wait(BAR(B_KRDY + 2 * kv + a));
        e_bulk_st(g_kv + (size_t)(b * 2 + kv) * 16384 + a * 8192, PAGE(12 + 6 * kv + a), 8192);
        e_publish(C_K + 128 * kv + b);
        if (a == 1) SSTAMP(11 + kv);
      }
      late_units();
      SSTAMP(18 + a);
#pragma unroll 1
      for (int q = lane; q < 160; q += 32) {
        const int i = q - 112;
        if (i >= 0 && (a || i >= 42)) break;
        const uint32_t* p = &g_mod[i < 0 ? 1344 + 448 * a + q * 4 : i < 28 ? 896 + 112 * c4 + i * 4 : 2240 - 112 + 56 * c8 + i * 4];
        uint4 x;
        do { x = ld_relaxed4(p); } while ((mod_bad(x, ep << 16) >> 16) != 0 && --bud > 0);
        if (i < 0) put_mod4(sb + OFF_MOD2, q + 112 * a, x, 0x3F003F00u);
        else sts128(sb + OFF_GA + i * 16, make_uint4(x.x << 16, x.y << 16, x.z << 16, x.w << 16));
      }
      e_arrive(BAR(B_MOD2));
      SSTAMP(a ? 13 : 10);
      l2_prefetch((const uint8_t*)P.pwsp + (size_t)b * 65536 + a * 32768, 32768, lane);
      if (a) l2_prefetch((const uint8_t*)P.pwout + b * 6272, 6272, lane);
      mbar_wait(BAR(B_S3MMA));
      poll(C_X + hh, 16 * ep);
      SSTAMP(5 + a);
      asm volatile(ELECT("mbarrier.expect_tx.relaxed.cta.shared::cta.b64 [%0], 2048;") ::"r"(BAR(B_A4 + 7 * a)) : "memory");
      e_bulk_ld(sb + (a ? OFF_R5 : OFF_MOD1), g_st1 + hh * 256, 2048, BAR(B_A4 + 7 * a));
      rows(&P.x1, 7, 7 * a, 0, hh, B_A4 + 7 * a);
      SSTAMP(20 + a);
      mbar_wait(BAR(B_STG + a));
      e_bulk_st(g_z2t + ((size_t)hh * FH + 112 * c8) * 128, PAGE(a ? 7 : 2), 14336);
      e_bulk_red_f32(g_st2 + hh * 64, PAGE(a ? 7 : 2) + 14336, 512);
      e_bulk_st(g_s.zs + hh * 1024 + c8 * 128, PAGE(a ? 7 : 2) + 14848, 128);
      e_publish(C_Z + hh);
      e_arrive(BAR(B_STGDONE));
      SSTAMP(14 + a);
      mbar_wait(BAR(B_A4RD + 1));
      mbar_wait(BAR(B_RAW + a));
#pragma unroll 2
      for (int q = 8 * a; q < 8 * a + 8; q++) {
        const uint4 v = lds128(PAGE(26) + q * 512 + lane * 16);
        const float m0 = __uint_as_float(v.x) * (1.f / 896.f), m1 = __uint_as_float(v.z) * (1.f / 896.f);
        const float r0 = rsqrtf(fmaxf(fmaf(__uint_as_float(v.y), 1.f / 896.f, -m0 * m0), 0.f) + 1e-5f);
        const float r1 = rsqrtf(fmaxf(fmaf(__uint_as_float(v.w), 1.f / 896.f, -m1 * m1), 0.f) + 1e-5f);
        sts32(sb + OFF_R5 + (q * 64 + perm64(2 * lane)) * 2, pack2(r0, r1));
      }
      e_arrive(BAR(B_ST2 + a));
      SSTAMP(16 + a);
      mbar_wait(BAR(B_S5E + 15));
      poll(C_U + 2 * hh + kh, 16 * ep);
      SSTAMP(8 + a);
#pragma unroll 1
      for (int q = 0; q < 3; q++) {
        if (q == 1 && a) mbar_wait(BAR(B_XRD));
        if (q == 2) mbar_wait(BAR(B_A6RD + a));
        rows(&P.u, q == 0 ? 4 : q, 16 + 5 * a + (q == 1 ? 4 : 0), 448 * kh + (q ? 192 + 64 * q : 0), hh, B_A6 + 7 * a + (q ? 3 + q : 0));
      }
    }
    __syncwarp();
    asm volatile("barrier.cluster.wait.acquire.aligned;" ::: "memory");
  } else {
    ep = ld_relaxed(&g_epoch) + 1;
    asm volatile("setmaxnreg.inc.sync.aligned.u32 232;");
    const int a = warp >> 2, w = warp & 3, j = lane & 3, g = lane >> 2;
    const int r0 = 16 * w + g;
    const uint32_t lx = lane & 7, lhi = lane >> 4;
    uint32_t lda[4];
#pragma unroll
    for (int ks = 0; ks < 4; ks++) lda[ks] = sb + (16 * w + (lane & 15)) * 128 + (((2 * ks + lhi) ^ lx) << 4);
    const uint32_t peer = kh ^ 1;

    STAMP(1);
    if (a == 1) bar_arrive(4, 256);

    uint32_t qf[14];
    {
      uint32_t A[28][4];
      {
        float s2[2][4] = {}, q2[2][4] = {};
        uint32_t pv0 = 0, pv1 = 0;
#pragma unroll
        for (int c = 0; c < 7; c++) {
          if (c == 0) bar_sync(6, 288);
          if (c < 2) mbar_wait(BAR(B_X + c));
#pragma unroll
          for (int ks = 0; ks < 4; ks++) ldsm4(A[4 * c + ks], lda[ks] + a * PG + 2 * c * PG);
#pragma unroll
          for (int ks = 0; ks < 4; ks++) rowsum_mma(s2[ks & 1], A[4 * c + ks]);
          if (c == 0) {
            const float m0 = (s2[0][0] + s2[1][0]) * (1.f / 64.f), m1 = (s2[0][2] + s2[1][2]) * (1.f / 64.f);
            pv0 = pack2(m0, m0); pv1 = pack2(m1, m1);
          }
          if (c == 6) e_arrive(BAR(B_XFREE));
#pragma unroll
          for (int ks = 0; ks < 4; ks++) {
            uint32_t* x = A[4 * c + ks];
            x[0] = hsub2(x[0], pv0); x[1] = hsub2(x[1], pv1); x[2] = hsub2(x[2], pv0); x[3] = hsub2(x[3], pv1);
            uint32_t sq[4] = {hmul2(x[0], x[0]), hmul2(x[1], x[1]), hmul2(x[2], x[2]), hmul2(x[3], x[3])};
            rowsum_mma(q2[ks & 1], sq);
          }
        }
        STAMP(2);
        const float m0 = fmaf(s2[0][0] + s2[1][0], 1.f / 448.f, -bf_lo(pv0)), m1 = fmaf(s2[0][2] + s2[1][2], 1.f / 448.f, -bf_lo(pv1));
        const float rs0 = rsqrtf(fmaxf(fmaf(q2[0][0] + q2[1][0], 1.f / 448.f, -m0 * m0), 0.f) + 1e-5f);
        const float rs1 = rsqrtf(fmaxf(fmaf(q2[0][2] + q2[1][2], 1.f / 448.f, -m1 * m1), 0.f) + 1e-5f);
        const uint32_t rp0 = pack2(rs0, rs0), rp1 = pack2(rs1, rs1), nm0 = pack2(-m0 * rs0, -m0 * rs0), nm1 = pack2(-m1 * rs1, -m1 * rs1);
#pragma unroll
        for (int i = 0; i < 28; i++) {
          A[i][0] = hfma2(A[i][0], rp0, nm0); A[i][1] = hfma2(A[i][1], rp1, nm1); A[i][2] = hfma2(A[i][2], rp0, nm0); A[i][3] = hfma2(A[i][3], rp1, nm1);
        }
      }
      STAMP(3);
      bar_sync(7, 352);
      cluster_arrive();
      if (tid < 224) {
        uint4 x;
        do { x = ld_relaxed4(&g_mod[tid * 4]); } while ((mod_bad(x, ep << 16) >> 16) != 0 && --bud > 0);
        put_mod4(sb + OFF_MOD1, tid, x, 0x3F803F80u);
      }
      bar_sync(1, 256);
      STAMP(4);
#pragma unroll
      for (int h = 0; h < 14; h++) {
        uint4 cv = lds128(sb + OFF_MOD1 + j * 16 + h * 64), sv = lds128(sb + OFF_MOD1 + 896 + j * 16 + h * 64);
        uint32_t* p = A[2 * h]; uint32_t* q = A[2 * h + 1];
        p[0] = hfma2(p[0], cv.x, sv.x); p[1] = hfma2(p[1], cv.x, sv.x); p[2] = hfma2(p[2], cv.y, sv.y); p[3] = hfma2(p[3], cv.y, sv.y);
        q[0] = hfma2(q[0], cv.z, sv.z); q[1] = hfma2(q[1], cv.z, sv.z); q[2] = hfma2(q[2], cv.w, sv.w); q[3] = hfma2(q[3], cv.w, sv.w);
      }
      const uint32_t st_addr = sb + (12 + a) * PG + (16 * w + ((lane >> 3) & 1) * 8 + lx) * 128;
#pragma unroll 1
      for (int p = 0; p < 3; p++) {
        float acc[28];
        const uint32_t wb = (p == 0 ? 14 : p == 1 ? 21 : 0) * (PG / 16) + kh, wb6 = p == 1 ? PG / 16 + kh : wb;
        mbar_wait(BAR(B_WK + p));
        bar_sync(4 + a, 256);
        STAMP(21 + 3 * p);
        wg_fence();
#pragma unroll
        for (int i = 0; i < 28; i++) wg_rs56<1>(acc, A[i], desc(i < 24 ? wb : wb6, i * 2048, 0), i != 0);
        wg_commit();
        if (p < 2 || a == 0) bar_arrive(5 - a, 256);
        STAMP(22 + 3 * p);
        wg_wait<0>(); keep<28>(acc);
        STAMP(23 + 3 * p);
        e_arrive(BAR(B_KPASS + p));
#pragma unroll
        for (int i = 0; i < 14; i++) qf[i] = pack2(acc[2 * i], acc[2 * i + 1]);
        if (p < 2) {
          if (p == 1) mbar_wait(BAR(B_KPASS));
          const uint32_t fill = (p == 1 && !(j & 1)) ? 0x3F80u : 0u;
          const uint32_t ta = st_addr + p * 6 * PG;
          stsm4(ta + ((lhi ^ lx) << 4), qf[0], qf[1], qf[2], qf[3]);
          stsm4(ta + (((2 + lhi) ^ lx) << 4), qf[4], qf[5], j < 2 ? qf[6] : fill, j < 2 ? qf[7] : fill);
          stsm4(ta + (((4 + lhi) ^ lx) << 4), j < 2 ? fill : qf[6], j < 2 ? fill : qf[7], qf[8], qf[9]);
          stsm4(ta + (((6 + lhi) ^ lx) << 4), qf[10], qf[11], qf[12], qf[13]);
          fence_async_smem();
          e_arrive(BAR(B_KRDY + 2 * p + a)); e_arrive(BAR(B_KALL + p));
        }
        STAMP(5 + p);
      }
    }
    {
      const int q0 = 128 * rb + 64 * a;
      const float sc = 0.18898223650461362f * 1.4426950408889634f;
      const float ninf = __int_as_float(0xff800000);
      uint32_t ow[14];
      const int dd = r0 - 2 * j;
      mbar_wait(BAR(B_KALL));
      STAMP(8);
#pragma unroll 1
      for (int hd = 0; hd < 2; hd++) {
        const uint32_t kb = a * (PG / 16) + hd * 4;
        float sm[96], s0[32], s4[32];
        wg_fence();
#pragma unroll
        for (int ks = 0; ks < 2; ks++) {
          wg_rs64<0>(s0, qf + 4 * ks, desc(kb, 8 * PG + ks * 32, 16), ks);
          wg_rs64<0>(s4, qf + 4 * ks, desc(kb, 12 * PG + ks * 32, 16), ks);
          wg_rs192<0>(sm, qf + 4 * ks, desc(kb, 9 * PG + ks * 32, 16), ks);
        }
        wg_commit();
        wg_wait<0>(); keep<96>(sm); keep<32>(s0); keep<32>(s4);
        STAMP(30 + 5 * hd);
#pragma unroll
        for (int i = 0; i < 8; i++) qf[i] = qf[i + 6];
        if (q0 < 256) {
#pragma unroll
          for (int i = 0; i < 32; i++) s0[i] = ninf;
        }
#pragma unroll
        for (int i = 0; i < 32; i++) { int t = i >> 2, e = (i >> 1) & 1, f = i & 1; s4[i] = (8 * t + f - 8 * e <= dd) ? s4[i] : s0[i]; }
        float mx[2] = {s4[0], s4[2]};
#pragma unroll
        for (int i = 0; i < 32; i++) mx[(i >> 1) & 1] = fmaxf(mx[(i >> 1) & 1], s4[i]);
#pragma unroll
        for (int k = 0; k < 3; k++) {
          float t[2] = {sm[32 * k], sm[32 * k + 2]};
#pragma unroll
          for (int i = 0; i < 32; i++) t[(i >> 1) & 1] = fmaxf(t[(i >> 1) & 1], sm[32 * k + i]);
          if (q0 - 192 + 64 * k >= 0) { mx[0] = fmaxf(mx[0], t[0]); mx[1] = fmaxf(mx[1], t[1]); }
        }
        mx[0] = -quad_max(mx[0]) * sc; mx[1] = -quad_max(mx[1]) * sc;
        STAMP(31 + 5 * hd);
        if (hd == 0) mbar_wait(BAR(B_VALL));
        if (hd | a) mbar_wait(BAR(B_TURN - 1 + 2 * hd + a));
        asm volatile("" : "+f"(mx[0]), "+f"(mx[1]) :: "memory");
        STAMP(33 + 5 * hd);
        uint32_t pm[48], p0[16], p4[16];
#pragma unroll
        for (int k = 0; k < 3; k++) {
          const bool ok = q0 - 192 + 64 * k >= 0;
          const float m0 = ok ? mx[0] : ninf, m1 = ok ? mx[1] : ninf;
#pragma unroll
          for (int i = 16 * k; i < 16 * k + 16; i++) {
            const float m = (i & 1) ? m1 : m0;
            pm[i] = pack2(ex2v(fmaf(sm[2 * i], sc, m)), ex2v(fmaf(sm[2 * i + 1], sc, m)));
          }
        }
#pragma unroll
        for (int i = 0; i < 16; i++) {
          const uint32_t pw = pack2(ex2v(fmaf(s4[2 * i], sc, mx[i & 1])), ex2v(fmaf(s4[2 * i + 1], sc, mx[i & 1])));
          const int lim = 8 * (i >> 1) - 8 * (i & 1);
          const uint32_t mk = (lim + 1 <= dd) ? 0xFFFFFFFFu : (lim <= dd ? 0x0000FFFFu : 0u);
          p4[i] = pw & mk; p0[i] = pw & ~mk;
        }
        float o[16];
        wg_fence();
        if (hd == 0 || a == 0) {
          const uint32_t dep = (pm[3] | pm[9] | pm[15]) | (pm[21] | pm[27] | pm[33]) | (pm[39] | pm[45] | p4[2]) | (p0[7] | p4[12] | p0[15]);
          __syncwarp();
          if (lane == 0) mbar_arrive(BAR(B_TURN + 2 * hd + a) + ((dep >> 31) << 3));
        }
        STAMP(32 + 5 * hd);
#pragma unroll
        for (int s = 0; s < 12; s++) wg_rs32<1>(o, pm + 4 * s, desc(kb, 15 * PG + s * 2048, 0), s);
#pragma unroll
        for (int s = 0; s < 4; s++) wg_rs32<1>(o, p0 + 4 * s, desc(kb, 14 * PG + s * 2048, 0), 1);
#pragma unroll
        for (int s = 0; s < 4; s++) wg_rs32<1>(o, p4 + 4 * s, desc(kb, 18 * PG + s * 2048, 0), 1);
        wg_commit();
        wg_wait<0>(); keep<16>(o);
        STAMP(34 + 5 * hd);
        const int src = (lane & 28) | (hd ? 0 : 2);
        const float l0 = rcp(__shfl_sync(~0u, hd ? o[0] : o[12], src)), l1 = rcp(__shfl_sync(~0u, hd ? o[2] : o[14], src));
        const bool keep3 = hd == 1 && j < 2;
        const uint32_t e0 = ow[12], e1 = ow[13];
#pragma unroll
        for (int i = 0; i < 6; i++) ow[i] = ow[i + 6];
#pragma unroll
        for (int t = 0; t < 4; t++) { ow[6 + 2 * t] = pack2(o[4 * t] * l0, o[4 * t + 1] * l0); ow[7 + 2 * t] = pack2(o[4 * t + 2] * l1, o[4 * t + 3] * l1); }
        ow[6] = keep3 ? e0 : ow[6]; ow[7] = keep3 ? e1 : ow[7];
      }
      const uint32_t stg = PAGE(8 + 5 * a) + w * 2048;
      store_rows<7>(ow, stg, g_o + (size_t)(q0 + 16 * w) * DM + 56 * c8, DM, lane);
      if (w == 0 && lane < 4) stg128(g_st2 + q0 + 8 * c8 + 2 * lane, make_uint4(0, 0, 0, 0));
      STAMP(48);
      e_release(C_O + 2 * rb + a);
      e_arrive(BAR(B_ATT));
    }
    STAMP(9);
    if (a == (cb4 & 1)) {
      const size_t off = (size_t)(64 * h3 + r0) * DM + 112 * c4 + 2 * j;
      uint32_t xr[28];
#pragma unroll
      for (int t = 0; t < 14; t++) { xr[2 * t] = __ldg((const uint32_t*)(P.px + off + 8 * t)); xr[2 * t + 1] = __ldg((const uint32_t*)(P.px + off + 8 * DM + 8 * t)); }
      float acc[56];
      mbar_wait(BAR(B_WO));
#pragma unroll 1
      for (int c = 0; c < 7; c++) {
        mbar_wait(BAR(B_A3 + c));
        if (c == 0) STAMP(10);
        wg_fence();
#pragma unroll
        for (int ks = 0; ks < 4; ks++) wg_ss112<1>(acc, desc(c * (PG / 16), 8 * PG + ks * 32, 16), desc((c < 4 ? 2 * c : 2 * c + 12) * (PG / 16), ks * 2048, PG), (c | ks) != 0);
      }
      wg_commit();
      mbar_wait(BAR(B_MOD2));
      wg_wait<0>(); keep<56>(acc);
      STAMP(40);
      e_arrive(BAR(B_S3MMA));
#pragma unroll
      for (int t = 0; t < 14; t++) {
        float2 ga = lds64f(sb + OFF_GA + j * 8 + t * 32);
        xr[2 * t] = pack2(fmaf(ga.x, acc[4 * t], bf_lo(xr[2 * t])), fmaf(ga.y, acc[4 * t + 1], bf_hi(xr[2 * t])));
        xr[2 * t + 1] = pack2(fmaf(ga.x, acc[4 * t + 2], bf_lo(xr[2 * t + 1])), fmaf(ga.y, acc[4 * t + 3], bf_hi(xr[2 * t + 1])));
      }
      const uint32_t stg = PAGE(7 * a) + w * 4096;
      store_rows<14>(xr, stg, g_x1 + (size_t)(64 * h3 + 16 * w) * DM + 112 * c4, DM, lane);
      float2 st0, st1;
      tile_stats(xr, st0, st1);
      if (j < 2) g_st1[(h3 * 4 + c4) * 64 + r0 + 8 * j] = j ? st1 : st0;
      STAMP(41);
      e_release(C_X + h3);
    }
    STAMP(11);
    uint32_t zp[28];
    {
      uint32_t A[28][4];
      mbar_wait(BAR(B_MOD2));
      uint32_t rh[2], rl[2], mr[2];
      mbar_wait(BAR(B_A4 + 7 * a));
#pragma unroll
      for (int e = 0; e < 2; e++) {
        float2 q[4];
#pragma unroll
        for (int i = 0; i < 4; i++) q[i] = lds64f(sb + (a ? OFF_R5 : OFF_MOD1) + (r0 + 8 * e) * 8 + i * 512);
        const float mean = (q[0].x + q[1].x + q[2].x + q[3].x) * (1.f / 448.f);
        float m2 = q[0].y + q[1].y + q[2].y + q[3].y;
#pragma unroll
        for (int i = 0; i < 4; i++) { const float d = fmaf(q[i].x, 1.f / 112.f, -mean); m2 = fmaf(112.f * d, d, m2); }
        const float rstd = rsqrtf(fmaxf(m2, 0.f) * (1.f / 448.f) + 1e-5f);
        rh[e] = pack2(rstd, rstd);
        const float lo = rstd - bf_lo(rh[e]), nm = -mean * rstd;
        rl[e] = pack2(lo, lo); mr[e] = pack2(nm, nm);
      }
      if (a == 1) bar_arrive(4, 256);
#pragma unroll
      for (int c = 0; c < 7; c++) {
        if (c) mbar_wait(BAR(B_A4 + 7 * a + c));
        if (c == 0) STAMP(12);
#pragma unroll
        for (int ks = 0; ks < 4; ks++) ldsm4(A[4 * c + ks], lda[ks] + 7 * a * PG + c * PG);
        if (c == 6) e_arrive(BAR(B_A4RD + a));
        if (c == 1 && a == 0) e_arrive(BAR(B_A4E));
#pragma unroll
        for (int h = 0; h < 2; h++) {
          uint4 cv = lds128(sb + OFF_MOD2 + j * 16 + (2 * c + h) * 64), sv = lds128(sb + OFF_MOD2 + 896 + j * 16 + (2 * c + h) * 64);
          uint32_t cw[4] = {cv.x, cv.y, cv.z, cv.w}, sw[4] = {sv.x, sv.y, sv.z, sv.w};
#pragma unroll
          for (int i = 0; i < 8; i++) {
            uint32_t& x = A[4 * c + 2 * h + (i >> 2)][i & 3];
            x = hfma2(hfma2(x, rh[i & 1], hfma2(x, rl[i & 1], mr[i & 1])), cw[i >> 1], sw[i >> 1]);
          }
        }
      }
      STAMP(49);
#pragma unroll 1
      for (int p = 0; p < 2; p++) {
        float acc[56];
        mbar_wait(BAR(B_Z2W + 3 * p));
        bar_sync(4 + a, 256);
        STAMP(50 + p);
#pragma unroll
        for (int c = 0; c < 7; c++) {
          if (c == 2 || c == 4) { if (p) mbar_wait(BAR(B_Z1W + c / 2)); }
          if (c == 3 || c == 6) { if (!p) mbar_wait(BAR(B_Z2W + c / 3)); }
          wg_fence();
          const int q2 = c < 2 ? 16 + 2 * c : c == 2 ? 15 : c < 6 ? 14 + 2 * c : 0, l2 = c == 2 ? 11 : 1;
          const int q1 = c == 0 ? 4 : c == 1 ? 6 : c == 2 ? 9 : c == 3 ? 11 : c == 4 ? 16 : c == 5 ? 18 : 0, l1 = c == 1 ? 8 : 1;
          const uint32_t d16 = p ? (q1 * (PG / 16)) | (l1 * (PG / 16)) << 16 : (q2 * (PG / 16)) | (l2 * (PG / 16)) << 16;
#pragma unroll
          for (int ks = 0; ks < 4; ks++) wg_rs112<1>(acc, A[4 * c + ks], desc(d16, ks * 2048, 0), (c | ks) != 0);
          wg_commit();
          if (c == 3) { wg_wait<2>(); e_arrive(BAR(B_Z2C + p)); }
          if (c == 5) { wg_wait<2>(); if (p) e_arrive(BAR(B_Z1C + 1)); }
        }
        if (p == 0 || a == 0) bar_arrive(5 - a, 256);
        wg_wait<1>();
        if (p) e_arrive(BAR(B_Z1C + 2));
        wg_wait<0>(); keep<56>(acc);
        if (!p) e_arrive(BAR(B_Z2PASS));
        STAMP(13 + 2 * p);
#pragma unroll
        for (int i = 0; i < 28; i++) zp[i] = pack2(gelu_h(acc[2 * i]), gelu_h(acc[2 * i + 1]));
        if (p == 0) {
          const uint32_t sp = PAGE(a ? 7 : 2), stg = sp + (lhi * 8 + lx) * 128 + (((2 * w + ((lane >> 3) & 1)) ^ lx) << 4);
#pragma unroll
          for (int t = 0; t < 7; t++) stsm4t(stg + t * 2048, zp[4 * t], zp[4 * t + 1], zp[4 * t + 2], zp[4 * t + 3]);
          float s2[2][4] = {}, q2[2][4] = {};
#pragma unroll
          for (int t = 0; t < 7; t++) {
            uint32_t sq[4] = {hmul2(zp[4 * t], zp[4 * t]), hmul2(zp[4 * t + 1], zp[4 * t + 1]), hmul2(zp[4 * t + 2], zp[4 * t + 2]), hmul2(zp[4 * t + 3], zp[4 * t + 3])};
            rowsum_mma(s2[t & 1], zp + 4 * t);
            rowsum_mma(q2[t & 1], sq);
          }
          if (j < 2) {
            const float sv = j ? s2[0][2] + s2[1][2] : s2[0][0] + s2[1][0], qv = j ? q2[0][2] + q2[1][2] : q2[0][0] + q2[1][0];
            sts64f(sp + 14336 + (r0 + 8 * j) * 8, sv, qv);
            sts16(sp + 14848 + (((2 * w + j) ^ c8) << 4) + g * 2, pack2(sv * (1.f / 896.f), 0.f));
          }
          fence_async_smem();
          e_arrive(BAR(B_STG + a));
          STAMP(14);
        }
      }
    }
    STAMP(16);
    {
      float acc[116];
      uint32_t A[2][16];
      const size_t row = 128 * rb + 64 * a + r0;
      const float bs0 = __bfloat162float(P.pbsp[row]), bs1 = __bfloat162float(P.pbsp[row + 8]);
      auto prep = [&](int i, uint32_t* Af) {
        if ((i & 7) == 0) {
          mbar_wait(BAR(B_ST2 + (i >> 3)));
          if (i) {
            asm volatile("barrier.cluster.wait.acquire.aligned;" ::: "memory");
            e_arrive_remote(mapa(BAR(B_X5FREE), peer));
          }
        }
        mbar_wait(BAR(B_S5F + i));
        const int s = i & 3;
        const uint32_t pa = PG * (s == 0 ? 20 : 6 * s - 4) + a * PG;
#pragma unroll
        for (int ks = 0; ks < 4; ks++) ldsm4(Af + 4 * ks, lda[ks] + pa);
#pragma unroll
        for (int h = 0; h < 2; h++) {
          uint4 rv = lds128(sb + OFF_R5 + i * 128 + j * 32 + h * 16);
          uint32_t* p = Af + 8 * h;
          p[0] = hmul2(p[0], rv.x); p[1] = hmul2(p[1], rv.x); p[2] = hmul2(p[2], rv.y); p[3] = hmul2(p[3], rv.y);
          p[4] = hmul2(p[4], rv.z); p[5] = hmul2(p[5], rv.z); p[6] = hmul2(p[6], rv.w); p[7] = hmul2(p[7], rv.w);
        }
      };
      auto mma = [&](int i, const uint32_t* Af) {
        const int s = i & 3;
        wg_fence();
#pragma unroll
        for (int ks = 0; ks < 4; ks++) wg_rs232<0>(acc, Af + 4 * ks, desc((s == 0 ? 22 : 6 * s - 2) * (PG / 16), ks * 32, 16), (i | ks) != 0);
        wg_commit();
        wg_wait<1>();
        if (i > 0) e_arrive(BAR(B_S5E + i - 1));
      };
#pragma unroll 1
      for (int i = 0; i < 16; i += 2) {
        if (i > 0) mma(i - 1, A[1]);
        prep(i, A[0]);
        STAMP(i == 0 ? 17 : 52 + (i >> 1));
        mma(i, A[0]);
        prep(i + 1, A[1]);
      }
      mma(15, A[1]);
      mbar_wait(BAR(B_X5FREE));
      wg_wait<0>(); keep<116>(acc);
      float c0 = quad_sum(acc[112] + acc[113]), c1 = quad_sum(acc[114] + acc[115]);
      e_arrive(BAR(B_S5E + 15));
      STAMP(18);
      const uint32_t xw = (a ? OFF_XB5_1 : OFF_XB5_0) + w * 3584, xoff = xw + lane * 16;
      const uint32_t rx = mapa(sb + xoff, peer), rbar = mapa(BAR(B_XB5 + a), peer);
#pragma unroll
      for (int q = 0; q < 7; q++) {
        const float* s = acc + 56 + 8 * q;
        st_async4(rx + q * 512, pack2(s[0] - c0, s[1] - c0), pack2(s[2] - c1, s[3] - c1), pack2(s[4] - c0, s[5] - c0), pack2(s[6] - c1, s[7] - c1), rbar);
      }
      c0 = bs0 - c0; c1 = bs1 - c1;
      uint32_t gk[28];
#pragma unroll
      for (int i = 0; i < 28; i++) { const float cc = (i & 1) ? c1 : c0; gk[i] = pack2(acc[2 * i] + cc, acc[2 * i + 1] + cc); }
      STAMP(42);
      mbar_wait(BAR(B_XB5 + a));
      STAMP(43);
#pragma unroll
      for (int q = 0; q < 7; q++) {
        const uint4 v = lds128(sb + xoff + q * 512);
        zp[4 * q] = hmul2(hadd2(gk[4 * q], v.x), zp[4 * q]); zp[4 * q + 1] = hmul2(hadd2(gk[4 * q + 1], v.y), zp[4 * q + 1]);
        zp[4 * q + 2] = hmul2(hadd2(gk[4 * q + 2], v.z), zp[4 * q + 2]); zp[4 * q + 3] = hmul2(hadd2(gk[4 * q + 3], v.w), zp[4 * q + 3]);
      }
      __syncwarp();
      store_rows<14>(zp, sb + xw, g_u + (size_t)(128 * rb + 64 * a + 16 * w) * FH + 112 * c8, FH, lane);
      STAMP(44);
      e_release(C_U + (2 * rb + a) * 2 + (c8 >> 2));
      e_arrive_remote(mapa(BAR(B_X6FREE), peer));
      if (a == 1) e_arrive(BAR(B_XRD));
    }
    STAMP(19);
    {
      const size_t off = (size_t)(128 * rb + 64 * a + r0) * DM + 56 * c8 + 2 * j;
      uint32_t xr[14];
#pragma unroll
      for (int t = 0; t < 7; t++) { xr[2 * t] = __ldcg((const uint32_t*)(g_x1 + off + 8 * t)); xr[2 * t + 1] = __ldcg((const uint32_t*)(g_x1 + off + 8 * DM + 8 * t)); }
      float acc[56];
      uint32_t A[2][16];
      auto ld6 = [&](int c, uint32_t* Af) {
        mbar_wait(BAR(B_A6 + 7 * a + c));
#pragma unroll
        for (int ks = 0; ks < 4; ks++) ldsm4(Af + 4 * ks, lda[ks] + (16 + 5 * a + (c < 5 ? c : c - 5)) * PG);
      };
      auto mma6 = [&](int c, const uint32_t* Af) {
        wg_fence();
#pragma unroll
        for (int ks = 0; ks < 4; ks++) wg_rs112<1>(acc, Af + 4 * ks, desc(c * (PG / 8), 2 * PG + ks * 2048, PG), (c | ks) != 0);
        wg_commit();
        wg_wait<1>();
      };
      mbar_wait(BAR(B_B6)); mbar_wait(BAR(B_B6 + 1)); mbar_wait(BAR(B_B6 + 2));
#pragma unroll 1
      for (int c = 0; c < 7; c += 2) {
        if (c) mma6(c - 1, A[1]);
        ld6(c, A[0]);
        if (c == 0) STAMP(45);
        mma6(c, A[0]);
        if (c < 6) ld6(c + 1, A[1]);
        if (c == 0) e_arrive(BAR(B_A6RD + a));
      }
      mbar_wait(BAR(B_X6FREE));
      wg_wait<0>(); keep<56>(acc);
      STAMP(46);
      float as[28], ak[28];
#pragma unroll
      for (int i = 0; i < 28; i++) { as[i] = kh ? acc[i] : acc[28 + i]; ak[i] = kh ? acc[28 + i] : acc[i]; }
      const uint32_t xw = a * PG + w * 2048, xoff = xw + lane * 16;
      const uint32_t rx = mapa(sb + xoff, peer), rbar = mapa(BAR(B_XB6 + a), peer);
#pragma unroll
      for (int q = 0; q < 3; q++) {
        const float* s = as + 8 * q;
        st_async4(rx + q * 512, pack2(s[0], s[1]), pack2(s[2], s[3]), pack2(s[4], s[5]), pack2(s[6], s[7]), rbar);
      }
      st_async2(rx + 1536 - lane * 8, pack2(as[24], as[25]), pack2(as[26], as[27]), rbar);
      mbar_wait(BAR(B_XB6 + a));
      STAMP(47);
      uint32_t vw[14];
#pragma unroll
      for (int q = 0; q < 3; q++) { uint4 v = lds128(sb + xoff + q * 512); vw[4 * q] = v.x; vw[4 * q + 1] = v.y; vw[4 * q + 2] = v.z; vw[4 * q + 3] = v.w; }
      { float2 v = lds64f(sb + xw + 1536 + lane * 8); vw[12] = __float_as_uint(v.x); vw[13] = __float_as_uint(v.y); }
#pragma unroll
      for (int t = 0; t < 7; t++) {
        float2 gb = lds64f(sb + OFF_GB + j * 8 + t * 32);
        xr[2 * t] = pack2(fmaf(gb.x, ak[4 * t] + bf_lo(vw[2 * t]), bf_lo(xr[2 * t])), fmaf(gb.y, ak[4 * t + 1] + bf_hi(vw[2 * t]), bf_hi(xr[2 * t])));
        xr[2 * t + 1] = pack2(fmaf(gb.x, ak[4 * t + 2] + bf_lo(vw[2 * t + 1]), bf_lo(xr[2 * t + 1])), fmaf(gb.y, ak[4 * t + 3] + bf_hi(vw[2 * t + 1]), bf_hi(xr[2 * t + 1])));
      }
      __syncwarp();
      store_rows<7>(xr, sb + xw, P.out + (size_t)(128 * rb + 64 * a + 16 * w) * DM + 56 * c8, DM, lane);
    }
    if (b == 0 && tid == 0) st_relaxed(&g_epoch, ep);
  }
}

typedef CUresult (*EncodeFn)(CUtensorMap*, CUtensorMapDataType, cuuint32_t, void*, const cuuint64_t*, const cuuint64_t*, const cuuint32_t*,
                             const cuuint32_t*, CUtensorMapInterleave, CUtensorMapSwizzle, CUtensorMapL2promotion, CUtensorMapFloatOOBfill);

void make_map(EncodeFn enc, CUtensorMap* m, const void* ptr, uint64_t inner, uint64_t outer, uint32_t bi, uint32_t bo,
              CUtensorMapSwizzle sw = CU_TENSOR_MAP_SWIZZLE_128B) {
  cuuint64_t dims[2] = {inner, outer}, strides[1] = {inner * 2};
  cuuint32_t box[2] = {bi, bo}, es[2] = {1, 1};
  enc(m, CU_TENSOR_MAP_DATA_TYPE_BFLOAT16, 2, const_cast<void*>(ptr), dims, strides, box, es, CU_TENSOR_MAP_INTERLEAVE_NONE,
      sw, CU_TENSOR_MAP_L2_PROMOTION_L2_256B, CU_TENSOR_MAP_FLOAT_OOB_FILL_NONE);
}

}

extern "C" void kernel_launch(void* const* d_in, const int* in_sizes, int n_in, void* d_out, int out_size) {
  static EncodeFn enc = nullptr;
  static void *po, *px1, *pu;
  if (!enc) {
    void* fn = nullptr;
    cudaDriverEntryPointQueryResult st;
    cudaGetDriverEntryPoint("cuTensorMapEncodeTiled", &fn, cudaEnableDefault, &st);
    enc = (EncodeFn)fn;
    cudaGetSymbolAddress(&po, g_o);
    cudaGetSymbolAddress(&px1, g_x1);
    cudaGetSymbolAddress(&pu, g_u);
    cudaFuncSetAttribute(fused_kernel, cudaFuncAttributeMaxDynamicSharedMemorySize, SMEM_BYTES);
  }
  typedef const __nv_bfloat16* bp;
  Params P;
  P.px = (bp)d_in[0]; P.pwqkv = (bp)d_in[1]; P.pwo = (bp)d_in[2]; P.pwin = (bp)d_in[4]; P.pwsp = (bp)d_in[5]; P.pbsp = (bp)d_in[6];
  P.pwout = (bp)d_in[7]; P.pc = (bp)d_in[8]; P.pwmod = (bp)d_in[9]; P.out = (__nv_bfloat16*)d_out;
  make_map(enc, &P.x, d_in[0], DM, SEQ, 64, 128);
  make_map(enc, &P.wqkv, d_in[1], 3 * DM, DM, 64, 64);
  make_map(enc, &P.wo64, d_in[2], DM, DM, 64, 64);
  make_map(enc, &P.wo48, d_in[2], DM, DM, 48, 64);
  make_map(enc, &P.win64, d_in[4], 2 * FH, DM, 64, 64);
  make_map(enc, &P.win48, d_in[4], 2 * FH, DM, 48, 64);
  make_map(enc, &P.wsp, d_in[5], SEQ, SEQ, 64, 128);
  make_map(enc, &P.wout64, d_in[7], DM, FH, 64, 64);
  make_map(enc, &P.wout48, d_in[7], DM, FH, 48, 64);
  make_map(enc, &P.o, po, DM, SEQ, 64, 64);
  make_map(enc, &P.x1, px1, DM, SEQ, 64, 64);
  make_map(enc, &P.u, pu, FH, SEQ, 64, 64);
  fused_kernel<<<128, 384, SMEM_BYTES, cudaStreamPerThread>>>(P);
}
```

```cpp
#include <cuda_runtime.h>
#include <cuda_bf16.h>
#include <cuda.h>
#include <stdint.h>

namespace {

constexpr int SEQ = 2048, DM = 448, FH = 896;
constexpr uint32_t PG = 8192;
constexpr uint32_t MISC = 27 * PG;
constexpr uint32_t OFF_MW = MISC;
constexpr uint32_t OFF_MOD1 = MISC + 3072;
constexpr uint32_t OFF_MOD2 = OFF_MOD1 + 2048;
constexpr uint32_t OFF_GA = OFF_MOD2 + 1792;
constexpr uint32_t OFF_GB = OFF_GA + 224;
constexpr uint32_t OFF_R5 = OFF_GB + 112;
constexpr uint32_t OFF_RED = OFF_R5 + 2048;
constexpr uint32_t OFF_BAR = OFF_RED + 256;
constexpr uint32_t SMEM_BYTES = OFF_BAR + 896;
constexpr uint32_t OFF_RAW1B = 14 * PG;
constexpr uint32_t OFF_XB5_0 = 0;
constexpr uint32_t OFF_XB5_1 = 25 * PG + 5120;
static_assert(SMEM_BYTES <= 232448, "smem");

enum : int {
  B_WK = 0, B_WV, B_WQ, B_WO, B_Z2W  , B_Z1W = B_Z2W + 3  , B_B6 = B_Z1W + 3  , B_ST2 = B_B6 + 3  ,
  B_XB5 = B_ST2 + 2  , B_XB6 = B_XB5 + 2  , B_RAW = B_XB6 + 2  , B_X = B_RAW + 2  , B_A3 = B_X, B_A4 = B_A3 + 7  , B_MW = B_A4 + 14, B_S5F  , B_END1 = B_S5F + 4,
  B_CNT2 = 48, B_STGDONE = B_CNT2, B_MOD2,
  B_CNT4 = 60, B_A4RD = B_CNT4  , B_STG = B_A4RD + 2  , B_A6RD = B_STG + 2  , B_KRDY = B_A6RD + 2  ,
  B_A4E = B_KRDY + 4, B_XRD, B_TURN  , B_END4 = B_TURN + 3,
  B_CNT8 = 84, B_XFREE = B_CNT8, B_KPASS, B_VPASS, B_QPASS, B_ATT, B_Z2PASS, B_Z2C, B_Z1C  , B_S5E = B_Z1C + 3  ,
  B_X5FREE = B_S5E + 4, B_X6FREE, B_KALL, B_VALL, B_XFREE2, B_ATT2, B_S3MMA, B_S3MMA2, B_END8,
  B_COUNT = 108,
  PH1 = 128
};
static_assert(B_XB5 >= 12 && B_RAW + 2 <= 24 && B_X5FREE >= 96 && B_END1 <= B_CNT2 && B_END4 <= B_CNT8 && B_END8 <= B_COUNT, "barriers");

constexpr int C_K = 0  , C_O = 256, C_X = 288, C_Z = 320, C_U = 352, C_COUNT = 416;

#define WGATE 1
constexpr int MODREP = 16;
struct Small {
  uint32_t epoch, pad[31];
  uint32_t mod[MODREP * 2688];
  uint32_t cnt[C_COUNT * 8];
  float2 st2[SEQ];
  uint8_t zs[32 * 1024];
  float2 st1[SEQ * 8];
};
__device__ __align__(1024) Small g_s;
#define g_epoch g_s.epoch
#define g_mod g_s.mod
#define g_cnt g_s.cnt
#define g_st1 g_s.st1
#define g_st2 g_s.st2
__device__ __align__(1024) uint8_t g_kv[16 * 8 * 2 * 16384];
__device__ __align__(1024) __nv_bfloat16 g_o[SEQ * DM];
__device__ __align__(1024) __nv_bfloat16 g_x1[SEQ * DM];
__device__ __align__(1024) __nv_bfloat16 g_u[SEQ * FH];
__device__ __align__(1024) uint8_t g_z2t[32 * FH * 128];
#define STAMP(i) do {} while (0)
#define SSTAMP(i) do {} while (0)

struct Params {
  CUtensorMap wmods, wmod, x, wsp, wqkv, wo64, wo48, win64, win48, wout64, wout48, o, x1, u;
  const __nv_bfloat16 *px, *pwqkv, *pwo, *pwin, *pwsp, *pbsp, *pwout, *pc, *pwmod;
  __nv_bfloat16* out;
};

__device__ __forceinline__ uint32_t smem_u32(const void* p) { return (uint32_t)__cvta_generic_to_shared(p); }
__device__ __forceinline__ void mbar_init(uint32_t bar, uint32_t cnt) { asm volatile("mbarrier.init.shared::cta.b64 [%0], %1;" ::"r"(bar), "r"(cnt)); }
__device__ __forceinline__ void mbar_expect(uint32_t bar, uint32_t bytes) { asm volatile("mbarrier.arrive.expect_tx.shared::cta.b64 _, [%0], %1;" ::"r"(bar), "r"(bytes) : "memory"); }
__device__ __forceinline__ void mbar_arrive(uint32_t bar) { asm volatile("mbarrier.arrive.shared::cta.b64 _, [%0];" ::"r"(bar) : "memory"); }
__device__ __forceinline__ void mbar_arrive_remote(uint32_t rbar) { asm volatile("mbarrier.arrive.shared::cluster.b64 _, [%0];" ::"r"(rbar) : "memory"); }
__device__ __forceinline__ uint32_t mapa(uint32_t addr, uint32_t cta) { uint32_t r; asm volatile("mapa.shared::cluster.u32 %0, %1, %2;" : "=r"(r) : "r"(addr), "r"(cta)); return r; }
__device__ __forceinline__ void mbar_wait2(uint32_t bar, uint32_t par, int& bud) {
  asm volatile("{\n.reg .pred p;\nWLOOP:\nmbarrier.try_wait.parity.shared::cta.b64 p, [%1], %2;\n@p bra WDONE;\n"
               "add.s32 %0, %0, -1;\nsetp.gt.s32 p, %0, 0;\n@p bra WLOOP;\nWDONE:\n}" : "+r"(bud) : "r"(bar), "r"(par) : "memory");
}
__device__ __forceinline__ void bar_sync(int id, int n) { asm volatile("bar.sync %0, %1;" ::"r"(id), "r"(n) : "memory"); }
__device__ __forceinline__ void bar_arrive(int id, int n) { asm volatile("bar.arrive %0, %1;" ::"r"(id), "r"(n) : "memory"); }
__device__ __forceinline__ void fence_async_smem() { asm volatile("fence.proxy.async.shared::cta;" ::: "memory"); }
__device__ __forceinline__ void fence_async_glob() { asm volatile("fence.proxy.async.global;" ::: "memory"); }
#define ELECT(body) "{\n.reg .pred p;\nelect.sync _|p, 0xffffffff;\n@p " body "\n}"
__device__ __forceinline__ void e_expect(uint32_t bar, uint32_t bytes) { asm volatile(ELECT("mbarrier.arrive.expect_tx.shared::cta.b64 _, [%0], %1;") ::"r"(bar), "r"(bytes) : "memory"); }
__device__ __forceinline__ void e_arrive(uint32_t bar) { __syncwarp(); asm volatile(ELECT("mbarrier.arrive.shared::cta.b64 _, [%0];") ::"r"(bar) : "memory"); }
__device__ __forceinline__ void e_arrive_remote(uint32_t rbar) { asm volatile(ELECT("mbarrier.arrive.shared::cluster.b64 _, [%0];") ::"r"(rbar) : "memory"); }
__device__ __forceinline__ void e_tma2d(uint32_t dst, const CUtensorMap* map, int c0, int c1, uint32_t bar) {
  asm volatile(ELECT("cp.async.bulk.tensor.2d.shared::cluster.global.mbarrier::complete_tx::bytes [%0], [%1, {%3, %4}], [%2];")
               ::"r"(dst), "l"(map), "r"(bar), "r"(c0), "r"(c1) : "memory");
}
__device__ __forceinline__ void e_tma2d_mc(uint32_t dst, const CUtensorMap* map, int c0, int c1, uint32_t bar) {
  asm volatile(ELECT("cp.async.bulk.tensor.2d.shared::cluster.global.mbarrier::complete_tx::bytes.multicast::cluster [%0], [%1, {%3, %4}], [%2], %5;")
               ::"r"(dst), "l"(map), "r"(bar), "r"(c0), "r"(c1), "h"((uint16_t)3) : "memory");
}
__device__ __forceinline__ void bulk_ld(uint32_t dst, const void* src, uint32_t bytes, uint32_t bar) {
  asm volatile("cp.async.bulk.shared::cluster.global.mbarrier::complete_tx::bytes [%0], [%1], %2, [%3];"
               ::"r"(dst), "l"(src), "r"(bytes), "r"(bar) : "memory");
}
__device__ __forceinline__ void e_bulk_ld(uint32_t dst, const void* src, uint32_t bytes, uint32_t bar) {
  asm volatile(ELECT("cp.async.bulk.shared::cluster.global.mbarrier::complete_tx::bytes [%0], [%1], %2, [%3];")
               ::"r"(dst), "l"(src), "r"(bytes), "r"(bar) : "memory");
}
__device__ __forceinline__ void e_bulk_st(void* dst, uint32_t src, uint32_t bytes) {
  asm volatile(ELECT("cp.async.bulk.global.shared::cta.bulk_group [%0], [%1], %2;") ::"l"(dst), "r"(src), "r"(bytes) : "memory");
}
__device__ __forceinline__ void e_bulk_red_f32(void* dst, uint32_t src, uint32_t bytes) {
  asm volatile(ELECT("cp.reduce.async.bulk.global.shared::cta.bulk_group.add.f32 [%0], [%1], %2;") ::"l"(dst), "r"(src), "r"(bytes) : "memory");
}
__device__ __forceinline__ void e_tma2d_st(const CUtensorMap* map, int c0, int c1, uint32_t src) {
  asm volatile(ELECT("cp.async.bulk.tensor.2d.global.shared::cta.bulk_group [%0, {%2, %3}], [%1];") ::"l"(map), "r"(src), "r"(c0), "r"(c1) : "memory");
}
__device__ __forceinline__ void bulk_done() {
  asm volatile("cp.async.bulk.commit_group;" ::: "memory");
  asm volatile("cp.async.bulk.wait_group 0;" ::: "memory");
  __syncwarp();
}
__device__ __forceinline__ void l2_prefetch(const void* p, int bytes, int lane) {
#pragma unroll 1
  for (int o = lane * 128; o < bytes; o += 4096) asm volatile("prefetch.global.L2 [%0];" ::"l"((const uint8_t*)p + o) : "memory");
}
__device__ __forceinline__ void prefetch_map(const CUtensorMap* m) { asm volatile("prefetch.tensormap [%0];" ::"l"(m) : "memory"); }
__device__ __forceinline__ uint32_t ld_acquire(const uint32_t* p) { uint32_t v; asm volatile("ld.acquire.gpu.global.u32 %0, [%1];" : "=r"(v) : "l"(p) : "memory"); return v; }
__device__ __forceinline__ uint32_t ld_relaxed(const uint32_t* p) { uint32_t v; asm volatile("ld.relaxed.gpu.global.u32 %0, [%1];" : "=r"(v) : "l"(p) : "memory"); return v; }
__device__ __forceinline__ uint4 ld_relaxed4(const uint32_t* p) {
  uint4 v; asm volatile("ld.relaxed.gpu.global.v4.u32 {%0,%1,%2,%3}, [%4];" : "=r"(v.x), "=r"(v.y), "=r"(v.z), "=r"(v.w) : "l"(p) : "memory"); return v;
}
__device__ __forceinline__ void st_relaxed(uint32_t* p, uint32_t v) { asm volatile("st.relaxed.gpu.global.u32 [%0], %1;" ::"l"(p), "r"(v) : "memory"); }
__device__ __forceinline__ void e_release(int c) { __syncwarp(); asm volatile(ELECT("red.release.gpu.global.add.u32 [%0], 1;") ::"l"(&g_cnt[c * 8]) : "memory"); }
__device__ __forceinline__ void e_publish(int c) { bulk_done(); fence_async_glob(); e_release(c); }
__device__ __forceinline__ bool reached(int c, uint32_t target) { return (int)(ld_acquire(&g_cnt[c * 8]) - target) >= 0; }
__device__ __forceinline__ void ldsm4(uint32_t* r, uint32_t addr) {
  asm volatile("ldmatrix.sync.aligned.m8n8.x4.shared.b16 {%0,%1,%2,%3}, [%4];" : "=r"(r[0]), "=r"(r[1]), "=r"(r[2]), "=r"(r[3]) : "r"(addr) : "memory");
}
__device__ __forceinline__ void stsm4(uint32_t addr, uint32_t r0, uint32_t r1, uint32_t r2, uint32_t r3) {
  asm volatile("stmatrix.sync.aligned.m8n8.x4.shared.b16 [%0], {%1,%2,%3,%4};" ::"r"(addr), "r"(r0), "r"(r1), "r"(r2), "r"(r3) : "memory");
}
__device__ __forceinline__ void stsm2(uint32_t addr, uint32_t r0, uint32_t r1) {
  asm volatile("stmatrix.sync.aligned.m8n8.x2.shared.b16 [%0], {%1,%2};" ::"r"(addr), "r"(r0), "r"(r1) : "memory");
}
__device__ __forceinline__ void stsm4t(uint32_t addr, uint32_t r0, uint32_t r1, uint32_t r2, uint32_t r3) {
  asm volatile("stmatrix.sync.aligned.m8n8.x4.trans.shared.b16 [%0], {%1,%2,%3,%4};" ::"r"(addr), "r"(r0), "r"(r1), "r"(r2), "r"(r3) : "memory");
}
__device__ __forceinline__ uint4 lds128(uint32_t addr) {
  uint4 v; asm volatile("ld.shared.v4.u32 {%0,%1,%2,%3}, [%4];" : "=r"(v.x), "=r"(v.y), "=r"(v.z), "=r"(v.w) : "r"(addr) : "memory"); return v;
}
__device__ __forceinline__ float2 lds64f(uint32_t addr) {
  float2 v; asm volatile("ld.shared.v2.f32 {%0,%1}, [%2];" : "=f"(v.x), "=f"(v.y) : "r"(addr) : "memory"); return v;
}
__device__ __forceinline__ void sts16(uint32_t addr, uint32_t v) { asm volatile("st.shared.u16 [%0], %1;" ::"r"(addr), "h"((uint16_t)v) : "memory"); }
__device__ __forceinline__ void sts32(uint32_t addr, uint32_t v) { asm volatile("st.shared.u32 [%0], %1;" ::"r"(addr), "r"(v) : "memory"); }
__device__ __forceinline__ void sts64f(uint32_t addr, float x, float y) { asm volatile("st.shared.v2.f32 [%0], {%1,%2};" ::"r"(addr), "f"(x), "f"(y) : "memory"); }
__device__ __forceinline__ void sts32f(uint32_t addr, float v) { asm volatile("st.shared.f32 [%0], %1;" ::"r"(addr), "f"(v) : "memory"); }
__device__ __forceinline__ uint32_t lds32(uint32_t addr) { uint32_t v; asm volatile("ld.shared.u32 %0, [%1];" : "=r"(v) : "r"(addr) : "memory"); return v; }
__device__ __forceinline__ float lds32f(uint32_t addr) { float v; asm volatile("ld.shared.f32 %0, [%1];" : "=f"(v) : "r"(addr) : "memory"); return v; }
__device__ __forceinline__ void sts128(uint32_t addr, uint4 v) { asm volatile("st.shared.v4.u32 [%0], {%1,%2,%3,%4};" ::"r"(addr), "r"(v.x), "r"(v.y), "r"(v.z), "r"(v.w) : "memory"); }
__device__ __forceinline__ void st_async4(uint32_t raddr, uint32_t a, uint32_t b, uint32_t c, uint32_t d, uint32_t rbar) {
  asm volatile("st.async.shared::cluster.mbarrier::complete_tx::bytes.v4.b32 [%0], {%1,%2,%3,%4}, [%5];" ::"r"(raddr), "r"(a), "r"(b), "r"(c), "r"(d), "r"(rbar) : "memory");
}
__device__ __forceinline__ void st_async2(uint32_t raddr, uint32_t a, uint32_t b, uint32_t rbar) {
  asm volatile("st.async.shared::cluster.mbarrier::complete_tx::bytes.v2.b32 [%0], {%1,%2}, [%3];" ::"r"(raddr), "r"(a), "r"(b), "r"(rbar) : "memory");
}
__device__ __forceinline__ uint32_t pack2(float lo, float hi) { uint32_t r; asm("cvt.rn.bf16x2.f32 %0, %1, %2;" : "=r"(r) : "f"(hi), "f"(lo)); return r; }
__device__ __forceinline__ float bf_lo(uint32_t w) { return __uint_as_float(w << 16); }
__device__ __forceinline__ float bf_hi(uint32_t w) { return __uint_as_float(w & 0xFFFF0000u); }
__device__ __forceinline__ uint32_t hfma2(uint32_t a, uint32_t b, uint32_t c) { uint32_t r; asm("fma.rn.bf16x2 %0, %1, %2, %3;" : "=r"(r) : "r"(a), "r"(b), "r"(c)); return r; }
__device__ __forceinline__ uint32_t hmul2(uint32_t a, uint32_t b) { uint32_t r; asm("mul.rn.bf16x2 %0, %1, %2;" : "=r"(r) : "r"(a), "r"(b)); return r; }
__device__ __forceinline__ uint32_t hsub2(uint32_t a, uint32_t b) { uint32_t r; asm("sub.rn.bf16x2 %0, %1, %2;" : "=r"(r) : "r"(a), "r"(b)); return r; }
__device__ __forceinline__ float ex2v(float x) { float r; asm volatile("ex2.approx.ftz.f32 %0, %1;" : "=f"(r) : "f"(x)); return r; }
__device__ __forceinline__ void stg128(void* p, uint4 v) { asm volatile("st.global.v4.u32 [%0], {%1,%2,%3,%4};" ::"l"(p), "r"(v.x), "r"(v.y), "r"(v.z), "r"(v.w) : "memory"); }
__device__ __forceinline__ uint32_t hadd2(uint32_t a, uint32_t b) { uint32_t r; asm("add.rn.bf16x2 %0, %1, %2;" : "=r"(r) : "r"(a), "r"(b)); return r; }
__device__ __forceinline__ float ex2(float x) { float r; asm("ex2.approx.ftz.f32 %0, %1;" : "=f"(r) : "f"(x)); return r; }
__device__ __forceinline__ float gelu_h(float y) {
  float u = y * fmaf(8.f * 0.0356774081f, y * y, 2.f * 0.7978845608f), t;
  asm("tanh.approx.f32 %0, %1;" : "=f"(t) : "f"(u));
  return fmaf(y, t, y);
}
__device__ __forceinline__ float quad_sum(float v) { v += __shfl_xor_sync(~0u, v, 1); v += __shfl_xor_sync(~0u, v, 2); return v; }
__device__ __forceinline__ float quad_max(float v) { v = fmaxf(v, __shfl_xor_sync(~0u, v, 1)); v = fmaxf(v, __shfl_xor_sync(~0u, v, 2)); return v; }
__device__ __forceinline__ void rowsum_mma(float* c, const uint32_t* a) {
  asm volatile("mma.sync.aligned.m16n8k16.row.col.f32.bf16.bf16.f32 {%0,%1,%2,%3}, {%4,%5,%6,%7}, {%8,%8}, {%0,%1,%2,%3};"
               : "+f"(c[0]), "+f"(c[1]), "+f"(c[2]), "+f"(c[3]) : "r"(a[0]), "r"(a[1]), "r"(a[2]), "r"(a[3]), "r"(0x3F803F80u));
}
__device__ __forceinline__ void wg_fence() { asm volatile("wgmma.fence.sync.aligned;" ::: "memory"); }
__device__ __forceinline__ void wg_commit() { asm volatile("wgmma.commit_group.sync.aligned;" ::: "memory"); }
template <int N> __device__ __forceinline__ void wg_wait() { asm volatile("wgmma.wait_group.sync.aligned %0;" ::"n"(N) : "memory"); }
constexpr uint32_t SMEM0 = 1024;
__device__ __forceinline__ uint64_t desc(uint32_t rt16, uint32_t off, uint32_t lbo) {
  return (uint64_t)(rt16 + (((SMEM0 + off) >> 4) | ((lbo >> 4) << 16))) | ((uint64_t)0x40000040u << 32);
}
template <int N> __device__ __forceinline__ void keep(float* d) {
#pragma unroll
  for (int i = 0; i < N; i++) asm volatile("" : "+f"(d[i]));
}

template <int TB> __device__ __forceinline__ void wg_rs32(float* d, const uint32_t* a, uint64_t db, int sd) {
  asm volatile("{\n.reg .pred p;\nsetp.ne.b32 p, %21, 0;\n"
    "wgmma.mma_async.sync.aligned.m64n32k16.f32.bf16.bf16 {%0, %1, %2, %3, %4, %5, %6, %7, %8, %9, %10, %11, %12, %13, %14, %15}, {%16, %17, %18, %19}, %20, p, 1, 1, %22;\n}"
    : "+f"(d[0]), "+f"(d[1]), "+f"(d[2]), "+f"(d[3]), "+f"(d[4]), "+f"(d[5]), "+f"(d[6]), "+f"(d[7]), "+f"(d[8]), "+f"(d[9]), "+f"(d[10]), "+f"(d[11]), "+f"(d[12]), "+f"(d[13]), "+f"(d[14]), "+f"(d[15])
    : "r"(a[0]), "r"(a[1]), "r"(a[2]), "r"(a[3]), "l"(db), "r"(sd), "n"(TB));
}
template <int TB> __device__ __forceinline__ void wg_rs56(float* d, const uint32_t* a, uint64_t db, int sd) {
  asm volatile("{\n.reg .pred p;\nsetp.ne.b32 p, %33, 0;\n"
    "wgmma.mma_async.sync.aligned.m64n56k16.f32.bf16.bf16 {%0, %1, %2, %3, %4, %5, %6, %7, %8, %9, %10, %11, %12, %13, %14, %15, %16, %17, %18, %19, %20, %21, %22, %23, %24, %25, %26, %27}, {%28, %29, %30, %31}, %32, p, 1, 1, %34;\n}"
    : "+f"(d[0]), "+f"(d[1]), "+f"(d[2]), "+f"(d[3]), "+f"(d[4]), "+f"(d[5]), "+f"(d[6]), "+f"(d[7]), "+f"(d[8]), "+f"(d[9]), "+f"(d[10]), "+f"(d[11]), "+f"(d[12]), "+f"(d[13]), "+f"(d[14]), "+f"(d[15]), "+f"(d[16]), "+f"(d[17]), "+f"(d[18]), "+f"(d[19]), "+f"(d[20]), "+f"(d[21]), "+f"(d[22]), "+f"(d[23]), "+f"(d[24]), "+f"(d[25]), "+f"(d[26]), "+f"(d[27])
    : "r"(a[0]), "r"(a[1]), "r"(a[2]), "r"(a[3]), "l"(db), "r"(sd), "n"(TB));
}
template <int TB> __device__ __forceinline__ void wg_rs64(float* d, const uint32_t* a, uint64_t db, int sd) {
  asm volatile("{\n.reg .pred p;\nsetp.ne.b32 p, %37, 0;\n"
    "wgmma.mma_async.sync.aligned.m64n64k16.f32.bf16.bf16 {%0, %1, %2, %3, %4, %5, %6, %7, %8, %9, %10, %11, %12, %13, %14, %15, %16, %17, %18, %19, %20, %21, %22, %23, %24, %25, %26, %27, %28, %29, %30, %31}, {%32, %33, %34, %35}, %36, p, 1, 1, %38;\n}"
    : "+f"(d[0]), "+f"(d[1]), "+f"(d[2]), "+f"(d[3]), "+f"(d[4]), "+f"(d[5]), "+f"(d[6]), "+f"(d[7]), "+f"(d[8]), "+f"(d[9]), "+f"(d[10]), "+f"(d[11]), "+f"(d[12]), "+f"(d[13]), "+f"(d[14]), "+f"(d[15]), "+f"(d[16]), "+f"(d[17]), "+f"(d[18]), "+f"(d[19]), "+f"(d[20]), "+f"(d[21]), "+f"(d[22]), "+f"(d[23]), "+f"(d[24]), "+f"(d[25]), "+f"(d[26]), "+f"(d[27]), "+f"(d[28]), "+f"(d[29]), "+f"(d[30]), "+f"(d[31])
    : "r"(a[0]), "r"(a[1]), "r"(a[2]), "r"(a[3]), "l"(db), "r"(sd), "n"(TB));
}
template <int TB> __device__ __forceinline__ void wg_rs112(float* d, const uint32_t* a, uint64_t db, int sd) {
  asm volatile("{\n.reg .pred p;\nsetp.ne.b32 p, %61, 0;\n"
    "wgmma.mma_async.sync.aligned.m64n112k16.f32.bf16.bf16 {%0, %1, %2, %3, %4, %5, %6, %7, %8, %9, %10, %11, %12, %13, %14, %15, %16, %17, %18, %19, %20, %21, %22, %23, %24, %25, %26, %27, %28, %29, %30, %31, %32, %33, %34, %35, %36, %37, %38, %39, %40, %41, %42, %43, %44, %45, %46, %47, %48, %49, %50, %51, %52, %53, %54, %55}, {%56, %57, %58, %59}, %60, p, 1, 1, %62;\n}"
    : "+f"(d[0]), "+f"(d[1]), "+f"(d[2]), "+f"(d[3]), "+f"(d[4]), "+f"(d[5]), "+f"(d[6]), "+f"(d[7]), "+f"(d[8]), "+f"(d[9]), "+f"(d[10]), "+f"(d[11]), "+f"(d[12]), "+f"(d[13]), "+f"(d[14]), "+f"(d[15]), "+f"(d[16]), "+f"(d[17]), "+f"(d[18]), "+f"(d[19]), "+f"(d[20]), "+f"(d[21]), "+f"(d[22]), "+f"(d[23]), "+f"(d[24]), "+f"(d[25]), "+f"(d[26]), "+f"(d[27]), "+f"(d[28]), "+f"(d[29]), "+f"(d[30]), "+f"(d[31]), "+f"(d[32]), "+f"(d[33]), "+f"(d[34]), "+f"(d[35]), "+f"(d[36]), "+f"(d[37]), "+f"(d[38]), "+f"(d[39]), "+f"(d[40]), "+f"(d[41]), "+f"(d[42]), "+f"(d[43]), "+f"(d[44]), "+f"(d[45]), "+f"(d[46]), "+f"(d[47]), "+f"(d[48]), "+f"(d[49]), "+f"(d[50]), "+f"(d[51]), "+f"(d[52]), "+f"(d[53]), "+f"(d[54]), "+f"(d[55])
    : "r"(a[0]), "r"(a[1]), "r"(a[2]), "r"(a[3]), "l"(db), "r"(sd), "n"(TB));
}
template <int TB> __device__ __forceinline__ void wg_rs192(float* d, const uint32_t* a, uint64_t db, int sd) {
  asm volatile("{\n.reg .pred p;\nsetp.ne.b32 p, %101, 0;\n"
    "wgmma.mma_async.sync.aligned.m64n192k16.f32.bf16.bf16 {%0, %1, %2, %3, %4, %5, %6, %7, %8, %9, %10, %11, %12, %13, %14, %15, %16, %17, %18, %19, %20, %21, %22, %23, %24, %25, %26, %27, %28, %29, %30, %31, %32, %33, %34, %35, %36, %37, %38, %39, %40, %41, %42, %43, %44, %45, %46, %47, %48, %49, %50, %51, %52, %53, %54, %55, %56, %57, %58, %59, %60, %61, %62, %63, %64, %65, %66, %67, %68, %69, %70, %71, %72, %73, %74, %75, %76, %77, %78, %79, %80, %81, %82, %83, %84, %85, %86, %87, %88, %89, %90, %91, %92, %93, %94, %95}, {%96, %97, %98, %99}, %100, p, 1, 1, %102;\n}"
    : "+f"(d[0]), "+f"(d[1]), "+f"(d[2]), "+f"(d[3]), "+f"(d[4]), "+f"(d[5]), "+f"(d[6]), "+f"(d[7]), "+f"(d[8]), "+f"(d[9]), "+f"(d[10]), "+f"(d[11]), "+f"(d[12]), "+f"(d[13]), "+f"(d[14]), "+f"(d[15]), "+f"(d[16]), "+f"(d[17]), "+f"(d[18]), "+f"(d[19]), "+f"(d[20]), "+f"(d[21]), "+f"(d[22]), "+f"(d[23]), "+f"(d[24]), "+f"(d[25]), "+f"(d[26]), "+f"(d[27]), "+f"(d[28]), "+f"(d[29]), "+f"(d[30]), "+f"(d[31]), "+f"(d[32]), "+f"(d[33]), "+f"(d[34]), "+f"(d[35]), "+f"(d[36]), "+f"(d[37]), "+f"(d[38]), "+f"(d[39]), "+f"(d[40]), "+f"(d[41]), "+f"(d[42]), "+f"(d[43]), "+f"(d[44]), "+f"(d[45]), "+f"(d[46]), "+f"(d[47]), "+f"(d[48]), "+f"(d[49]), "+f"(d[50]), "+f"(d[51]), "+f"(d[52]), "+f"(d[53]), "+f"(d[54]), "+f"(d[55]), "+f"(d[56]), "+f"(d[57]), "+f"(d[58]), "+f"(d[59]), "+f"(d[60]), "+f"(d[61]), "+f"(d[62]), "+f"(d[63]), "+f"(d[64]), "+f"(d[65]), "+f"(d[66]), "+f"(d[67]), "+f"(d[68]), "+f"(d[69]), "+f"(d[70]), "+f"(d[71]), "+f"(d[72]), "+f"(d[73]), "+f"(d[74]), "+f"(d[75]), "+f"(d[76]), "+f"(d[77]), "+f"(d[78]), "+f"(d[79]), "+f"(d[80]), "+f"(d[81]), "+f"(d[82]), "+f"(d[83]), "+f"(d[84]), "+f"(d[85]), "+f"(d[86]), "+f"(d[87]), "+f"(d[88]), "+f"(d[89]), "+f"(d[90]), "+f"(d[91]), "+f"(d[92]), "+f"(d[93]), "+f"(d[94]), "+f"(d[95])
    : "r"(a[0]), "r"(a[1]), "r"(a[2]), "r"(a[3]), "l"(db), "r"(sd), "n"(TB));
}
template <int TB> __device__ __forceinline__ void wg_rs232(float* d, const uint32_t* a, uint64_t db, int sd) {
  asm volatile("{\n.reg .pred p;\nsetp.ne.b32 p, %121, 0;\n"
    "wgmma.mma_async.sync.aligned.m64n232k16.f32.bf16.bf16 {%0, %1, %2, %3, %4, %5, %6, %7, %8, %9, %10, %11, %12, %13, %14, %15, %16, %17, %18, %19, %20, %21, %22, %23, %24, %25, %26, %27, %28, %29, %30, %31, %32, %33, %34, %35, %36, %37, %38, %39, %40, %41, %42, %43, %44, %45, %46, %47, %48, %49, %50, %51, %52, %53, %54, %55, %56, %57, %58, %59, %60, %61, %62, %63, %64, %65, %66, %67, %68, %69, %70, %71, %72, %73, %74, %75, %76, %77, %78, %79, %80, %81, %82, %83, %84, %85, %86, %87, %88, %89, %90, %91, %92, %93, %94, %95, %96, %97, %98, %99, %100, %101, %102, %103, %104, %105, %106, %107, %108, %109, %110, %111, %112, %113, %114, %115}, {%116, %117, %118, %119}, %120, p, 1, 1, %122;\n}"
    : "+f"(d[0]), "+f"(d[1]), "+f"(d[2]), "+f"(d[3]), "+f"(d[4]), "+f"(d[5]), "+f"(d[6]), "+f"(d[7]), "+f"(d[8]), "+f"(d[9]), "+f"(d[10]), "+f"(d[11]), "+f"(d[12]), "+f"(d[13]), "+f"(d[14]), "+f"(d[15]), "+f"(d[16]), "+f"(d[17]), "+f"(d[18]), "+f"(d[19]), "+f"(d[20]), "+f"(d[21]), "+f"(d[22]), "+f"(d[23]), "+f"(d[24]), "+f"(d[25]), "+f"(d[26]), "+f"(d[27]), "+f"(d[28]), "+f"(d[29]), "+f"(d[30]), "+f"(d[31]), "+f"(d[32]), "+f"(d[33]), "+f"(d[34]), "+f"(d[35]), "+f"(d[36]), "+f"(d[37]), "+f"(d[38]), "+f"(d[39]), "+f"(d[40]), "+f"(d[41]), "+f"(d[42]), "+f"(d[43]), "+f"(d[44]), "+f"(d[45]), "+f"(d[46]), "+f"(d[47]), "+f"(d[48]), "+f"(d[49]), "+f"(d[50]), "+f"(d[51]), "+f"(d[52]), "+f"(d[53]), "+f"(d[54]), "+f"(d[55]), "+f"(d[56]), "+f"(d[57]), "+f"(d[58]), "+f"(d[59]), "+f"(d[60]), "+f"(d[61]), "+f"(d[62]), "+f"(d[63]), "+f"(d[64]), "+f"(d[65]), "+f"(d[66]), "+f"(d[67]), "+f"(d[68]), "+f"(d[69]), "+f"(d[70]), "+f"(d[71]), "+f"(d[72]), "+f"(d[73]), "+f"(d[74]), "+f"(d[75]), "+f"(d[76]), "+f"(d[77]), "+f"(d[78]), "+f"(d[79]), "+f"(d[80]), "+f"(d[81]), "+f"(d[82]), "+f"(d[83]), "+f"(d[84]), "+f"(d[85]), "+f"(d[86]), "+f"(d[87]), "+f"(d[88]), "+f"(d[89]), "+f"(d[90]), "+f"(d[91]), "+f"(d[92]), "+f"(d[93]), "+f"(d[94]), "+f"(d[95]), "+f"(d[96]), "+f"(d[97]), "+f"(d[98]), "+f"(d[99]), "+f"(d[100]), "+f"(d[101]), "+f"(d[102]), "+f"(d[103]), "+f"(d[104]), "+f"(d[105]), "+f"(d[106]), "+f"(d[107]), "+f"(d[108]), "+f"(d[109]), "+f"(d[110]), "+f"(d[111]), "+f"(d[112]), "+f"(d[113]), "+f"(d[114]), "+f"(d[115])
    : "r"(a[0]), "r"(a[1]), "r"(a[2]), "r"(a[3]), "l"(db), "r"(sd), "n"(TB));
}
template <int TB> __device__ __forceinline__ void wg_ss56(float* d, uint64_t da, uint64_t db, int sd) {
  asm volatile("{\n.reg .pred p;\nsetp.ne.b32 p, %30, 0;\n"
    "wgmma.mma_async.sync.aligned.m64n56k16.f32.bf16.bf16 {%0, %1, %2, %3, %4, %5, %6, %7, %8, %9, %10, %11, %12, %13, %14, %15, %16, %17, %18, %19, %20, %21, %22, %23, %24, %25, %26, %27}, %28, %29, p, 1, 1, 0, %31;\n}"
    : "+f"(d[0]), "+f"(d[1]), "+f"(d[2]), "+f"(d[3]), "+f"(d[4]), "+f"(d[5]), "+f"(d[6]), "+f"(d[7]), "+f"(d[8]), "+f"(d[9]), "+f"(d[10]), "+f"(d[11]), "+f"(d[12]), "+f"(d[13]), "+f"(d[14]), "+f"(d[15]), "+f"(d[16]), "+f"(d[17]), "+f"(d[18]), "+f"(d[19]), "+f"(d[20]), "+f"(d[21]), "+f"(d[22]), "+f"(d[23]), "+f"(d[24]), "+f"(d[25]), "+f"(d[26]), "+f"(d[27])
    : "l"(da), "l"(db), "r"(sd), "n"(TB));
}

__device__ __forceinline__ int perm448(int k) { return (k >> 5) * 32 + ((k & 7) >> 1) * 8 + ((k >> 4) & 1) * 4 + ((k >> 3) & 1) * 2 + (k & 1); }
__device__ __forceinline__ int perm64(int k) { return ((k & 7) >> 1) * 16 + (k >> 4) * 4 + ((k >> 3) & 1) * 2 + (k & 1); }

__device__ __forceinline__ float rcp(float x) { float r; asm("rcp.approx.ftz.f32 %0, %1;" : "=f"(r) : "f"(x)); return r; }
__device__ __forceinline__ float silu_bf(float c) { return bf_lo(pack2(c * rcp(1.f + ex2(-1.4426950408889634f * c)), 0.f)); }
__device__ __forceinline__ void fma8(float* acc, uint4 w, float s) {
  acc[0] = fmaf(bf_lo(w.x), s, acc[0]); acc[1] = fmaf(bf_hi(w.x), s, acc[1]);
  acc[2] = fmaf(bf_lo(w.y), s, acc[2]); acc[3] = fmaf(bf_hi(w.y), s, acc[3]);
  acc[4] = fmaf(bf_lo(w.z), s, acc[4]); acc[5] = fmaf(bf_hi(w.z), s, acc[5]);
  acc[6] = fmaf(bf_lo(w.w), s, acc[6]); acc[7] = fmaf(bf_hi(w.w), s, acc[7]);
}
__device__ __forceinline__ float warp_red8(float* v, int lane) {
  bool b4 = lane & 16, b3 = lane & 8, b2 = lane & 4;
  float t[4];
#pragma unroll
  for (int i = 0; i < 4; i++) { float keepv = b4 ? v[i + 4] : v[i], send = b4 ? v[i] : v[i + 4]; t[i] = keepv + __shfl_xor_sync(~0u, send, 16); }
  float u[2];
#pragma unroll
  for (int i = 0; i < 2; i++) { float keepv = b3 ? t[i + 2] : t[i], send = b3 ? t[i] : t[i + 2]; u[i] = keepv + __shfl_xor_sync(~0u, send, 8); }
  float keepv = b2 ? u[1] : u[0], send = b2 ? u[0] : u[1];
  float r = keepv + __shfl_xor_sync(~0u, send, 4);
  r += __shfl_xor_sync(~0u, r, 2);
  r += __shfl_xor_sync(~0u, r, 1);
  return r;
}

template <int NT> __device__ __forceinline__ void stage_rows(const uint32_t* w, uint32_t stg, int lane) {
  const uint32_t sa = stg + (lane & 15) * (NT * 16) + (lane >> 4) * 16;
#pragma unroll
  for (int t = 0; t + 1 < NT; t += 2) stsm4(sa + t * 16, w[2 * t], w[2 * t + 1], w[2 * t + 2], w[2 * t + 3]);
  if (NT & 1) stsm2(sa + (NT - 1) * 16, w[2 * NT - 2], w[2 * NT - 1]);
}
template <int NT> __device__ __forceinline__ void store_rows(const uint32_t* w, uint32_t stg, __nv_bfloat16* gp, int pitch, int lane) {
  stage_rows<NT>(w, stg, lane);
  __syncwarp();
  if (NT == 14) {
    const int r = lane >= 14, c = lane - 14 * r;
    gp += r * pitch + c * 8;
    if (lane < 28) {
#pragma unroll
      for (int k = 0; k < 8; k++) stg128(gp + 2 * k * pitch, lds128(stg + lane * 16 + k * 448));
    }
  } else {
    const int r = (lane * 37) >> 8, c = lane - 7 * r;
    gp += r * pitch + c * 8;
    if (lane < 28) {
#pragma unroll
      for (int k = 0; k < 4; k++) stg128(gp + 4 * k * pitch, lds128(stg + lane * 16 + k * 448));
    }
  }
}
__device__ __forceinline__ int st2pos(int h) { return ((h >> 4) * 16 + (h & 1) * 8 + ((h >> 1) & 7)) * 64; }
__device__ __forceinline__ uint32_t mod_bad(uint4 v, uint32_t tag) { return (v.x ^ tag) | (v.y ^ tag) | (v.z ^ tag) | (v.w ^ tag); }
__device__ __forceinline__ void put_mod4(uint32_t base, int i, uint4 v, uint32_t s2) {
  const bool isc = i >= 112;
  const float one = isc ? 1.f : 0.f;
  const int k = (isc ? i - 112 : i) * 4;
  base += (isc ? 0 : 896) + perm448(k) * 2;
  sts32(base, hmul2(pack2(bf_lo(v.x) + one, bf_lo(v.y) + one), s2));
  sts32(base + 16, hmul2(pack2(bf_lo(v.z) + one, bf_lo(v.w) + one), s2));
}

__host__ __device__ constexpr uint32_t bar_count(int i) { return i >= B_CNT8 ? 8 : i >= B_CNT4 ? 4 : i >= B_CNT2 ? 2 : 1; }
constexpr uint32_t WE(int wait, int p0, int p1, int full, int c, int type, int add, int n) {
  return (uint32_t)wait | p0 << 8 | p1 << 13 | full << 18 | c << 22 | type << 25 | add << 27 | (uint32_t)n << 29;
}
__constant__ uint32_t c_wprog[28] = {
  WE(B_VALL, 20, 21, B_WO, 4, 1, 0, 7), WE(0, 22, 23, B_WO, 5, 1, 0, 0), WE(0, 24, 25, B_WO, 6, 1, 0, 0),
  WE(B_QPASS, 0, 1, B_WO, 0, 1, 0, 0), WE(0, 2, 3, B_WO, 1, 1, 0, 0), WE(0, 4, 5, B_WO, 2, 1, 0, 0), WE(0, 6, 7, B_WO, 3, 1, 0, 0),
  WE(PH1 + B_A3 + 6, 16, 17, B_Z2W, 0, 2, 2, 3), WE(0, 18, 19, B_Z2W, 1, 2, 2, 0), WE(0, 15, 26, B_Z2W, 2, 2, 2, 0),
  WE(B_A4 + 5, 20, 21, B_Z2W + 1, 3, 2, 2, 3), WE(0, 22, 23, B_Z2W + 1, 4, 2, 2, 0), WE(0, 24, 25, B_Z2W + 1, 5, 2, 2, 0),
  WE(B_A4E, 0, 1, B_Z2W + 2, 6, 2, 2, 1),
  WE(B_A4RD, 4, 5, B_Z1W, 0, 2, 0, 2), WE(B_A4RD + 1, 6, 14, B_Z1W, 1, 2, 0, 0),
  WE(0, 9, 10, B_Z1W + 1, 2, 2, 0, 2), WE(0, 11, 12, B_Z1W + 1, 3, 2, 0, 0),
  WE(B_Z2C, 16, 17, B_Z1W + 2, 4, 2, 0, 3), WE(0, 18, 19, B_Z1W + 2, 5, 2, 0, 0), WE(B_Z2PASS, 0, 1, B_Z1W + 2, 6, 2, 0, 0),
  WE(PH1 + B_KPASS, 2, 3, B_B6, 0, 3, 0, 3), WE(0, 4, 5, B_B6, 1, 3, 0, 0), WE(0, 6, 7, B_B6, 2, 3, 0, 0),
  WE(PH1 + B_VPASS, 8, 9, B_B6 + 1, 3, 3, 0, 3), WE(0, 10, 11, B_B6 + 1, 4, 3, 0, 0), WE(0, 12, 13, B_B6 + 1, 5, 3, 0, 0),
  WE(PH1 + B_QPASS, 14, 15, B_B6 + 2, 6, 3, 0, 1)};

__global__ void __cluster_dims__(2, 1, 1) __launch_bounds__(384, 1) fused_kernel(const __grid_constant__ Params P) {
  extern __shared__ __align__(1024) uint8_t smem_raw[];
  const uint32_t sb = smem_u32(smem_raw);
  const int tid = threadIdx.x, lane = tid & 31, warp = __shfl_sync(~0u, tid >> 5, 0);
  const int b = blockIdx.x, rb = b >> 3, c8 = b & 7, cb4 = c8 >> 1, kh = c8 & 1;
  const int h3 = 2 * rb + (cb4 & 1), c4 = 2 * (cb4 >> 1) + kh;
  const int rb1 = 2 * (b >> 4) + kh, j1 = (b >> 1) & 7, b1 = rb1 * 8 + j1;
  const uint32_t peer = kh ^ 1;
  int bud = 1 << 20;
  auto BAR = [&](int i) { return sb + OFF_BAR + 8u * i; };
  auto PAGE = [&](int i) { return sb + PG * i; };
  auto mbar_wait = [&](uint32_t bar, uint32_t par = 0) { mbar_wait2(bar, par, bud); };
  auto poll = [&](int c, uint32_t target) { while (!__all_sync(~0u, reached(c, target)) && --bud > 0) {} fence_async_glob(); };

  if (blockIdx.x >= 128) {
    float* tab = (float*)(smem_raw + 200704);
    const int rg = min(tid / 56, 5), cg = tid - 56 * (tid / 56), col0 = 448 * (b - 126);
    if (tid == 0) mbar_init(BAR(0), 1);
    __syncthreads();
    const uint32_t tg = (ld_relaxed(&g_epoch) + 1) << 16;
    float acc[8] = {0, 0, 0, 0, 0, 0, 0, 0};
#pragma unroll 1
    for (int h = 0; h < 2; h++) {
      if (warp == 0) {
        e_expect(BAR(0), 200704);
        e_tma2d(sb, &P.wmods, col0, 224 * h, BAR(0));
        e_tma2d(sb + 100352, &P.wmods, col0 + 224, 224 * h, BAR(0));
      }
      if (tid < 224) tab[tid] = silu_bf(bf_lo(__ldg((const uint16_t*)P.pc + 224 * h + tid)));
      __syncthreads();
      mbar_wait(BAR(0), h);
#pragma unroll 2
      for (int k = rg; k < 224; k += 6) fma8(acc, lds128(sb + (cg >= 28 ? 100352 - 448 : 0) + k * 448 + cg * 16), tab[k]);
      __syncthreads();
    }
    if (tid < 336) {
#pragma unroll
      for (int i = 0; i < 8; i++) tab[512 + rg * 448 + cg * 8 + i] = acc[i];
    }
    __syncthreads();
    for (int c = tid; c < 448; c += 384) {
      float v = 0.f;
#pragma unroll
      for (int i = 0; i < 6; i++) v += tab[512 + i * 448 + c];
#pragma unroll 1
      for (int r = 0; r < MODREP; r++) st_relaxed(&g_mod[r * 2688 + col0 + c], (pack2(v, 0.f) & 0xFFFFu) | tg);
    }
    return;
  }
  STAMP(0);
  if ((sb & 0xFFFFFFu) != SMEM0) bud = 0;
  uint32_t ep = 0;
  if (warp <= 8) {
    if (lane == 0) {
      const uint32_t cnt = bar_count(12 * warp);
#pragma unroll
      for (int i = 0; i < 12; i++) mbar_init(BAR(12 * warp + i), cnt);
      asm volatile("fence.mbarrier_init.release.cluster;" ::: "memory");
    }
    __syncwarp();
    if (warp == 1) {
#pragma unroll
      for (int i = 0; i < 6; i++) e_expect(BAR(B_XB5 + i), i < 2 ? 14336 : i < 4 ? 7168 : 4096);
    }
    if (warp == 8) {
      asm volatile(ELECT("mbarrier.expect_tx.relaxed.cta.shared::cta.b64 [%0], %1;") ::"r"(BAR(B_KALL)), "r"(min(rb1, 2) * 16384) : "memory");
      asm volatile(ELECT("mbarrier.expect_tx.relaxed.cta.shared::cta.b64 [%0], %1;") ::"r"(BAR(B_VALL)), "r"(min(rb1, 2) * 16384) : "memory");
    }
    bar_arrive(10, 384);
    bar_sync(6, 288);
  }
  auto cluster_wait = [&]() { asm volatile("barrier.cluster.wait.acquire.aligned;" ::: "memory"); };
  auto cluster_arrive = [&]() { asm volatile("barrier.cluster.arrive.relaxed.aligned;" ::: "memory"); };

  if (warp >= 8) {
    asm volatile("setmaxnreg.dec.sync.aligned.u32 56;");
    auto rows = [&](const CUtensorMap* m, int n, int page, int col, int hh, int bar) {
#pragma unroll 1
      for (int c = 0; c < n; c++) { e_expect(BAR(bar + c), 8192); e_tma2d(PAGE(page + c), m, col + 64 * c, 64 * hh, BAR(bar + c)); }
    };
    auto rows_mc = [&](const CUtensorMap* m, int page, int hh, int bar, int par) {
#pragma unroll 1
      for (int c = par; c < 7; c += 2) e_tma2d_mc(PAGE(page + c), m, 64 * c, 64 * hh, BAR(bar + c));
    };
    const int a = warp - 10, hh = 2 * rb + a;
    if (warp > 8) {
      const int t96 = tid - 288;
      {
        uint16_t cc[5];
#pragma unroll
        for (int q = 0; q < 5; q++) cc[q] = t96 + 96 * q < 448 ? __ldg((const uint16_t*)P.pc + t96 + 96 * q) : (uint16_t)0;
        const uint32_t e0 = ld_relaxed(&g_epoch);
        if (warp == 9 && lane < 13) prefetch_map(&P.wmod + lane);
        cluster_arrive();
        bar_sync(10, 384);
        mbar_wait(BAR(B_MW));
        float acc[8] = {0, 0, 0, 0, 0, 0, 0, 0};
#pragma unroll
        for (int q = 0; q < 5; q++) fma8(acc, lds128(sb + OFF_MW + min(t96 + 96 * q, 447) * 16), silu_bf(bf_lo(cc[q])));
        ep = __shfl_sync(~0u, e0, 0) + 1;
        const float r = warp_red8(acc, lane);
        if (!(lane & 3)) sts32f(sb + OFF_RED + (warp - 9) * 32 + lane, r);
        bar_sync(9, 96);
        if (b < 112) {
          const uint32_t red = sb + OFF_RED + (t96 & 7) * 4;
          const uint32_t v = (pack2(lds32f(red) + lds32f(red + 32) + lds32f(red + 64), 0.f) & 0xFFFFu) | (ep << 16);
#pragma unroll 1
          for (int r = t96 >> 3; r < MODREP; r += 12) st_relaxed(&g_mod[r * 2688 + 8 * b + (t96 & 7)], v);
        }
        SSTAMP(36);
      }
#pragma unroll 1
      for (int st = 0; st < 3; st++) {
        if (st != 1) {
          if (st && warp == 9) break;
          mbar_wait(BAR(st ? B_WO : B_X + 6));
          bool first = !st;
          const uint32_t* gm = g_mod + rb * 2688;
          const int nt = st ? 64 : 96, ni = st ? 265 : 223;
#pragma unroll 1
          for (int i0 = st ? t96 - 32 : t96; i0 <= ni; i0 += 192) {
            uint4 x[3];
            uint32_t bad;
            do {
              bad = 0;
#pragma unroll
              for (int q = 0; q < 3; q++) {
                const int i = min(i0 + nt * q, ni) - 224;
                x[q] = ld_relaxed4(&gm[i < 0 ? 672 * st + 896 + i * 4 : i < 28 ? 896 + 112 * c4 + i * 4 : 2240 - 112 + 56 * c8 + i * 4]);
              }
              if (first) { bar_arrive(11, 128); first = false; }
#pragma unroll
              for (int q = 0; q < 3; q++) bad |= mod_bad(x[q], ep << 16);
            } while (__any_sync(~0u, (bad >> 16) != 0) && --bud > 0);
#pragma unroll 1
            for (int q = 0; q < 3; q++) {
              const int i = min(i0 + nt * q, ni) - 224;
              if (i < 0) put_mod4(sb + (st ? OFF_MOD2 : OFF_MOD1), i + 224, x[0], st ? 0x3F003F00u : 0x3F803F80u);
              else { sts32(sb + OFF_GA + i * 8, __byte_perm(x[0].x, x[0].y, 0x5410)); sts32(sb + OFF_GA + i * 8 + 4, __byte_perm(x[0].z, x[0].w, 0x5410)); }
              x[0] = x[1]; x[1] = x[2];
            }
            if (!st) break;
          }
          __syncwarp();
          SSTAMP(st ? 13 : 37);
          if (st) { e_arrive(BAR(B_MOD2)); break; }
          __syncwarp();
          bar_arrive(1, 384);
          if (warp > 9) l2_prefetch(a ? (const uint8_t*)P.pwin + b * 12544 : (const uint8_t*)P.pwo + b * 3136, a ? 12544 : 3136, lane);
        }
        const int kv = st;
        if (warp > 9) {
          mbar_wait(BAR(B_KRDY + 2 * kv + a));
          e_bulk_st(g_kv + (size_t)(b1 * 2 + kv) * 16384 + a * 8192, PAGE(12 + 6 * kv + a), 8192);
          e_publish(C_K + 128 * kv + b1);
          if (a == 1) SSTAMP(11 + kv);
          continue;
        }
        const uint32_t dst = PAGE(8 + 6 * kv), bar = BAR(B_KALL + kv);
        mbar_wait(BAR(B_XFREE + kv));
        uint32_t todo = rb1 >= 2 ? 3 : rb1;
        while (todo) {
          const uint32_t m = (__ballot_sync(~0u, reached(C_K + 128 * kv + max(b1 - 8 - 8 * (lane & 1), 0), 2 * ep)) | (--bud <= 0 ? 3u : 0u)) & todo;
          if (!m) continue;
          fence_async_glob();
          const int d = (m & 1) ^ 1;
          e_bulk_ld(dst + (1 - d) * 16384, g_kv + (size_t)((b1 - 8 - 8 * d) * 2 + kv) * 16384, 16384, bar);
          SSTAMP(2 * kv + d);
          todo &= ~(1u << d);
        }
      }
    }
    if (warp == 8) {
      e_expect(BAR(B_MW), 7168);
      e_tma2d(sb + OFF_MW, &P.wmod, 8 * min(b, 111), 0, BAR(B_MW));
      e_tma2d(sb + OFF_MW + 3584, &P.wmod, 8 * min(b, 111), 224, BAR(B_MW));
#pragma unroll
      for (int c = 0; c < 7; c++) { e_expect(BAR(B_X + c), 16384); e_tma2d(PAGE(2 * c), &P.x, 64 * c, 128 * rb1, BAR(B_X + c)); }
      cluster_arrive();
      cluster_wait();
#pragma unroll 1
      for (int p = 0; p < 3; p++) {
        const int col = (56 * j1 & ~15) + (p == 2 ? 0 : 448 + 448 * p);
        e_expect(BAR(B_WK + p), 7 * 8192);
        if (p == 0) bar_sync(11, 128);
        if (p == 1) bar_sync(1, 384);
#pragma unroll 1
        for (int c = (p ^ kh) & 1; c < 7; c += 2) {
          if (c + 7 * p >= 13 && c + 7 * p < 16) { mbar_wait(BAR(B_XFREE)); mbar_wait(BAR(B_XFREE2)); }
          e_tma2d_mc(c + 7 * p == 13 ? PAGE(7) : PAGE((p == 0 ? 14 : p == 1 ? 21 : 0) + c), &P.wqkv, col, 64 * c, BAR(B_WK + p));
        }
        SSTAMP(44 + p);
      }
#pragma unroll 1
      for (int i = 0; i < 28; i++) {
        if (i == 7) {
          asm volatile(ELECT("cp.async.bulk.prefetch.L2.global [%0], 32768;") ::"l"((const uint8_t*)P.pwsp + (size_t)b * 65536) : "memory");
          asm volatile(ELECT("cp.async.bulk.prefetch.L2.global [%0], 32768;") ::"l"((const uint8_t*)P.pwsp + (size_t)b * 65536 + 32768) : "memory");
        }
        const uint32_t e = c_wprog[i], type = (e >> 25) & 3;
        if (e & 255) mbar_wait(BAR(e & 127), (e >> 7) & 1);
        const uint32_t bar = BAR((e >> 18) & 15);
        const int col = 112 * (type == 1 ? c4 : type == 2 ? c8 : cb4) + 448 * ((e >> 27) & 3);
        const int row = 64 * ((e >> 22) & 7) + (type == 3 ? 448 * kh : 0);
        const CUtensorMap* m = &P.wqkv + (2 * type - 1);
        if (e >> 29) e_expect(bar, (e >> 29) * 14336);
        e_tma2d(PAGE((e >> 8) & 31), m, col, row, bar);
        e_tma2d(PAGE((e >> 13) & 31), m + 1, col + (type == 1 ? 56 : 64), row, bar);
        if (i == 0) SSTAMP(49);
        if (i == 6) SSTAMP(50);
      }
    } else if (warp == 9) {
#pragma unroll
      for (int c = 0; c < 7; c++) e_expect(BAR(B_A3 + c), 8192);
      mbar_wait(BAR(B_ATT)); mbar_wait(BAR(B_ATT2));
      poll(C_O + h3, 8 * ep);
      SSTAMP(4);
      rows_mc(&P.o, 8, h3, B_A3, kh);
      l2_prefetch((const uint8_t*)P.pwout + b * 6272, 6272, lane);
      mbar_wait(BAR(B_Z2PASS));
#pragma unroll 1
      for (int i = 0; i < 16; i++) {
        const int s = i & 3, h = 16 * kh + (i < 8 ? 2 * i : 2 * i - 15);
        if (i == 0 || i == 3) {
          poll(C_Z + 16 * kh + 2 * (lane & 7) + (i & 1), 8 * ep);
          e_bulk_ld(PAGE(26) + (i & 1) * 4096, g_st2 + (2 * kh + (i & 1)) * 512, 4096, BAR(B_RAW + (i & 1)));
        }
        if (i == 1) mbar_wait(BAR(B_STGDONE));
        if (i) mbar_wait(BAR(i >= 4 ? B_S5E + s : B_Z1C + i - 1), i >= 4 ? (i >> 2) - 1 & 1 : 0);
        const uint32_t dst = PAGE(s == 0 ? 20 : 6 * s - 4);
        const uint8_t* src = g_z2t + (size_t)h * FH * 128;
        e_expect(BAR(B_S5F + s), 46080);
        e_tma2d(dst, &P.wsp, 64 * h, 128 * rb, BAR(B_S5F + s));
        e_bulk_ld(dst + 16384, src + 14336 * c8, 14336, BAR(B_S5F + s));
        e_bulk_ld(dst + 30720, src + 14336 * (c8 ^ 1), 14336, BAR(B_S5F + s));
        e_bulk_ld(dst + 45056, g_s.zs + h * 1024, 1024, BAR(B_S5F + s));
        if (i == 0) SSTAMP(7);
      }
    } else {
#pragma unroll
      for (int c = 0; c < 7; c++) e_expect(BAR(B_A4 + 7 * a + c), c ? 8192 : 12288);
      mbar_wait(BAR(B_S3MMA)); mbar_wait(BAR(B_S3MMA2));
      poll(C_X + hh, 8 * ep);
      SSTAMP(5 + a);
      e_bulk_ld(sb + (a ? OFF_RAW1B : OFF_MW), g_st1 + hh * 512, 4096, BAR(B_A4 + 7 * a));
      rows_mc(&P.x1, 7 * a, hh, B_A4 + 7 * a, kh ^ a);
      SSTAMP(20 + a);
      mbar_wait(BAR(B_STG + a));
      e_bulk_red_f32(g_st2 + st2pos(hh), PAGE(a ? 7 : 2) + 14336, 512);
      e_publish(C_Z + hh);
      e_arrive(BAR(B_STGDONE));
      SSTAMP(14 + a);
      mbar_wait(BAR(B_RAW + a));
#pragma unroll 1
      for (int q = 8 * a; q < 8 * a + 8; q++) {
        const uint4 v = lds128(PAGE(26) + q * 512 + lane * 16);
        const float m0 = __uint_as_float(v.x) * (1.f / 896.f), m1 = __uint_as_float(v.z) * (1.f / 896.f);
        const float r0 = rsqrtf(fmaxf(fmaf(__uint_as_float(v.y), 1.f / 896.f, -m0 * m0), 0.f) + 1e-5f);
        const float r1 = rsqrtf(fmaxf(fmaf(__uint_as_float(v.w), 1.f / 896.f, -m1 * m1), 0.f) + 1e-5f);
        sts32(sb + OFF_R5 + (q * 64 + perm64(2 * lane)) * 2, pack2(r0, r1));
      }
      e_arrive(BAR(B_ST2 + a));
      SSTAMP(16 + a);
      mbar_wait(BAR(B_QPASS), 1);
      poll(C_U + 2 * hh + kh, 4 * ep);
      SSTAMP(8 + a);
#pragma unroll 1
      for (int q = 0; q < 3; q++) {
        if (q == 1 && a) mbar_wait(BAR(B_XRD));
        if (q == 2) mbar_wait(BAR(B_A6RD + a));
        rows(&P.u, q == 0 ? 4 : q, 16 + 5 * a + (q == 1 ? 4 : 0), 448 * kh + (q ? 192 + 64 * q : 0), hh, B_A4 + 7 * a + (q ? 3 + q : 0));
      }
    }
    __syncwarp();
    if (warp > 8) cluster_wait();
  } else {
    asm volatile("setmaxnreg.inc.sync.aligned.u32 224;");
    const int a = warp >> 2, w = warp & 3, j = lane & 3, g = lane >> 2;
    const int r0 = 16 * w + g;
    const uint32_t lx = lane & 7, lhi = lane >> 4;
    uint32_t lda[4];
#pragma unroll
    for (int ks = 0; ks < 4; ks++) lda[ks] = sb + (16 * w + (lane & 15)) * 128 + (((2 * ks + lhi) ^ lx) << 4);

    cluster_arrive();
    STAMP(1);
    if (a == 1) bar_arrive(4, 256);

    uint32_t qf[14];
    {
      uint32_t A[28][4];
      {
        float s2[2][4] = {}, q2[2][4] = {};
        uint32_t pv0 = 0, pv1 = 0;
#pragma unroll
        for (int c = 0; c < 7; c++) {
          mbar_wait(BAR(B_X + c));
          if (c == 0 || c == 6) STAMP(62 + (c > 0));
#pragma unroll
          for (int ks = 0; ks < 4; ks++) ldsm4(A[4 * c + ks], lda[ks] + a * PG + 2 * c * PG);
#pragma unroll
          for (int ks = 0; ks < 4; ks++) rowsum_mma(s2[ks & 1], A[4 * c + ks]);
          if (c == 0) {
            const float m0 = (s2[0][0] + s2[1][0]) * (1.f / 64.f), m1 = (s2[0][2] + s2[1][2]) * (1.f / 64.f);
            pv0 = pack2(m0, m0); pv1 = pack2(m1, m1);
          }
          if (c == 6) { e_arrive(BAR(B_XFREE)); cluster_wait(); e_arrive_remote(mapa(BAR(B_XFREE2), peer)); }
#pragma unroll
          for (int ks = 0; ks < 4; ks++) {
            uint32_t* x = A[4 * c + ks];
            x[0] = hsub2(x[0], pv0); x[1] = hsub2(x[1], pv1); x[2] = hsub2(x[2], pv0); x[3] = hsub2(x[3], pv1);
            uint32_t sq[4] = {hmul2(x[0], x[0]), hmul2(x[1], x[1]), hmul2(x[2], x[2]), hmul2(x[3], x[3])};
            rowsum_mma(q2[ks & 1], sq);
          }
        }
        STAMP(2);
        const float m0 = fmaf(s2[0][0] + s2[1][0], 1.f / 448.f, -bf_lo(pv0)), m1 = fmaf(s2[0][2] + s2[1][2], 1.f / 448.f, -bf_lo(pv1));
        const float rs0 = rsqrtf(fmaxf(fmaf(q2[0][0] + q2[1][0], 1.f / 448.f, -m0 * m0), 0.f) + 1e-5f);
        const float rs1 = rsqrtf(fmaxf(fmaf(q2[0][2] + q2[1][2], 1.f / 448.f, -m1 * m1), 0.f) + 1e-5f);
        const uint32_t rp0 = pack2(rs0, rs0), rp1 = pack2(rs1, rs1), nm0 = pack2(-m0 * rs0, -m0 * rs0), nm1 = pack2(-m1 * rs1, -m1 * rs1);
#pragma unroll
        for (int i = 0; i < 28; i++) {
          A[i][0] = hfma2(A[i][0], rp0, nm0); A[i][1] = hfma2(A[i][1], rp1, nm1); A[i][2] = hfma2(A[i][2], rp0, nm0); A[i][3] = hfma2(A[i][3], rp1, nm1);
        }
      }
      STAMP(3);
      bar_sync(1, 384);
      if (a == 1) bar_sync(7, 256);
      STAMP(4);
#pragma unroll
      for (int h = 0; h < 14; h++) {
        uint4 cv = lds128(sb + OFF_MOD1 + j * 16 + h * 64), sv = lds128(sb + OFF_MOD1 + 896 + j * 16 + h * 64);
        uint32_t* p = A[2 * h]; uint32_t* q = A[2 * h + 1];
        p[0] = hfma2(p[0], cv.x, sv.x); p[1] = hfma2(p[1], cv.x, sv.x); p[2] = hfma2(p[2], cv.y, sv.y); p[3] = hfma2(p[3], cv.y, sv.y);
        q[0] = hfma2(q[0], cv.z, sv.z); q[1] = hfma2(q[1], cv.z, sv.z); q[2] = hfma2(q[2], cv.w, sv.w); q[3] = hfma2(q[3], cv.w, sv.w);
      }
      if (a == 0) asm volatile("bar.arrive 7, 256;" ::"r"(A[27][3]), "r"(A[20][0]), "r"(A[13][1]) : "memory");
      const uint32_t st_addr = sb + (12 + a) * PG + (16 * w + ((lane >> 3) & 1) * 8 + lx) * 128;
#pragma unroll 1
      for (int p = 0; p < 3; p++) {
        float acc[28];
        const uint32_t wb = (p == 0 ? 14 : p == 1 ? 21 : 0) * (PG / 16) + (j1 & 1), wb6 = p == 1 ? PG / 16 + (j1 & 1) : wb;
        if (p == 0) STAMP(60);
        mbar_wait(BAR(B_WK + p));
        if (p == 0) STAMP(61);
        bar_sync(4 + a, 256);
        STAMP(21 + 3 * p);
        wg_fence();
#pragma unroll
        for (int i = 0; i < 28; i++) wg_rs56<1>(acc, A[i], desc(i < 24 ? wb : wb6, i * 2048, 0), i != 0);
        wg_commit();
        if (p < 2 || a == 0) bar_arrive(5 - a, 256);
        STAMP(22 + 3 * p);
        wg_wait<0>(); keep<28>(acc);
        STAMP(23 + 3 * p);
        e_arrive(BAR(B_KPASS + p));
#pragma unroll
        for (int i = 0; i < 14; i++) qf[i] = pack2(acc[2 * i], acc[2 * i + 1]);
        if (p < 2) {
          if (p == 1 || rb1 < 2) mbar_wait(BAR(B_XFREE + p));
          if (rb1 < 2) {
#pragma unroll 1
            for (int i = tid; i < (2 - rb1) * 1024; i += 256) sts128(PAGE(8 + 6 * p) + i * 16, make_uint4(0, 0, 0, 0));
          }
          const uint32_t fill = (p == 1 && !(j & 1)) ? 0x3F80u : 0u;
          const uint32_t ta = st_addr + p * 6 * PG;
          stsm4(ta + ((lhi ^ lx) << 4), qf[0], qf[1], qf[2], qf[3]);
          stsm4(ta + (((2 + lhi) ^ lx) << 4), qf[4], qf[5], j < 2 ? qf[6] : fill, j < 2 ? qf[7] : fill);
          stsm4(ta + (((4 + lhi) ^ lx) << 4), j < 2 ? fill : qf[6], j < 2 ? fill : qf[7], qf[8], qf[9]);
          stsm4(ta + (((6 + lhi) ^ lx) << 4), qf[10], qf[11], qf[12], qf[13]);
          fence_async_smem();
          e_arrive(BAR(B_KRDY + 2 * p + a)); e_arrive(BAR(B_KALL + p));
        }
        STAMP(5 + p);
      }
    }
    {
      const int q0 = 128 * rb1 + 64 * a;
      const float sc = 0.18898223650461362f * 1.4426950408889634f;
      const float ninf = __int_as_float(0xff800000);
      uint32_t ow[14];
      const int dd = r0 - 2 * j;
      mbar_wait(BAR(B_KALL));
      STAMP(8);
#pragma unroll 1
      for (int hd = 0; hd < 2; hd++) {
        const uint32_t kb = a * (PG / 16) + hd * 4;
        float sm[96], s0[32], s4[32];
        wg_fence();
#pragma unroll
        for (int ks = 0; ks < 2; ks++) {
          wg_rs64<0>(s0, qf + 4 * ks, desc(kb, 8 * PG + ks * 32, 16), ks);
          wg_rs64<0>(s4, qf + 4 * ks, desc(kb, 12 * PG + ks * 32, 16), ks);
          wg_rs192<0>(sm, qf + 4 * ks, desc(kb, 9 * PG + ks * 32, 16), ks);
        }
        wg_commit();
        wg_wait<0>(); keep<96>(sm); keep<32>(s0); keep<32>(s4);
        STAMP(30 + 5 * hd);
#pragma unroll
        for (int i = 0; i < 8; i++) qf[i] = qf[i + 6];
        if (q0 < 256) {
#pragma unroll
          for (int i = 0; i < 32; i++) s0[i] = ninf;
        }
#pragma unroll
        for (int i = 0; i < 32; i++) { int t = i >> 2, e = (i >> 1) & 1, f = i & 1; s4[i] = (8 * t + f - 8 * e <= dd) ? s4[i] : s0[i]; }
        float mx[2] = {s4[0], s4[2]};
#pragma unroll
        for (int i = 0; i < 32; i++) mx[(i >> 1) & 1] = fmaxf(mx[(i >> 1) & 1], s4[i]);
#pragma unroll
        for (int k = 0; k < 3; k++) {
          float t[2] = {sm[32 * k], sm[32 * k + 2]};
#pragma unroll
          for (int i = 0; i < 32; i++) t[(i >> 1) & 1] = fmaxf(t[(i >> 1) & 1], sm[32 * k + i]);
          if (q0 - 192 + 64 * k >= 0) { mx[0] = fmaxf(mx[0], t[0]); mx[1] = fmaxf(mx[1], t[1]); }
        }
        mx[0] = -quad_max(mx[0]) * sc; mx[1] = -quad_max(mx[1]) * sc;
        STAMP(31 + 5 * hd);
        if (hd | a) mbar_wait(BAR(B_TURN - 1 + 2 * hd + a));
        asm volatile("" : "+f"(mx[0]), "+f"(mx[1]) :: "memory");
        STAMP(33 + 5 * hd);
        uint32_t pm[48], p0[16], p4[16];
#pragma unroll
        for (int k = 0; k < 3; k++) {
          const bool ok = q0 - 192 + 64 * k >= 0;
          const float m0 = ok ? mx[0] : ninf, m1 = ok ? mx[1] : ninf;
#pragma unroll
          for (int i = 16 * k; i < 16 * k + 16; i++) {
            const float m = (i & 1) ? m1 : m0;
            pm[i] = pack2(ex2v(fmaf(sm[2 * i], sc, m)), ex2v(fmaf(sm[2 * i + 1], sc, m)));
          }
        }
#pragma unroll
        for (int i = 0; i < 16; i++) {
          const uint32_t pw = pack2(ex2v(fmaf(s4[2 * i], sc, mx[i & 1])), ex2v(fmaf(s4[2 * i + 1], sc, mx[i & 1])));
          const int lim = 8 * (i >> 1) - 8 * (i & 1);
          const uint32_t mk = (lim + 1 <= dd) ? 0xFFFFFFFFu : (lim <= dd ? 0x0000FFFFu : 0u);
          p4[i] = pw & mk; p0[i] = pw & ~mk;
        }
        if (hd == 0 || a == 0) {
          const uint32_t dep = (pm[3] | pm[9] | pm[15]) | (pm[21] | pm[27] | pm[33]) | (pm[39] | pm[45] | p4[2]) | (p0[7] | p4[12] | p0[15]);
          __syncwarp();
          if (lane == 0) mbar_arrive(BAR(B_TURN + 2 * hd + a) + ((dep >> 31) << 3));
        }
        if (hd == 0) mbar_wait(BAR(B_VALL));
        float o[16];
        wg_fence();
        STAMP(32 + 5 * hd);
#pragma unroll
        for (int s = 0; s < 12; s++) wg_rs32<1>(o, pm + 4 * s, desc(kb, 15 * PG + s * 2048, 0), s);
#pragma unroll
        for (int s = 0; s < 4; s++) wg_rs32<1>(o, p0 + 4 * s, desc(kb, 14 * PG + s * 2048, 0), 1);
#pragma unroll
        for (int s = 0; s < 4; s++) wg_rs32<1>(o, p4 + 4 * s, desc(kb, 18 * PG + s * 2048, 0), 1);
        wg_commit();
        wg_wait<0>(); keep<16>(o);
        STAMP(34 + 5 * hd);
        const int src = (lane & 28) | (hd ? 0 : 2);
        const float l0 = rcp(__shfl_sync(~0u, hd ? o[0] : o[12], src)), l1 = rcp(__shfl_sync(~0u, hd ? o[2] : o[14], src));
        const bool keep3 = hd == 1 && j < 2;
        const uint32_t e0 = ow[12], e1 = ow[13];
#pragma unroll
        for (int i = 0; i < 6; i++) ow[i] = ow[i + 6];
#pragma unroll
        for (int t = 0; t < 4; t++) { ow[6 + 2 * t] = pack2(o[4 * t] * l0, o[4 * t + 1] * l0); ow[7 + 2 * t] = pack2(o[4 * t + 2] * l1, o[4 * t + 3] * l1); }
        ow[6] = keep3 ? e0 : ow[6]; ow[7] = keep3 ? e1 : ow[7];
      }
      const uint32_t stg = PAGE(8 + 5 * a) + w * 2048;
      store_rows<7>(ow, stg, g_o + (size_t)(q0 + 16 * w) * DM + 56 * j1, DM, lane);
      if (w == 0 && lane < 4) stg128(g_st2 + st2pos(2 * rb1 + a) + 8 * j1 + 2 * lane, make_uint4(0, 0, 0, 0));
      STAMP(48);
      e_arrive(BAR(B_ATT)); e_arrive_remote(mapa(BAR(B_ATT2), peer));
      bar_sync(2 + a, 128);
      if (w == 0) e_release(C_O + 2 * rb1 + a);
    }
    STAMP(9);
    {
      const size_t off = (size_t)(64 * h3 + r0) * DM + 112 * c4 + 56 * a + 2 * j;
      uint32_t xr[16];
#pragma unroll
      for (int t = 0; t < 7; t++) { xr[2 * t] = __ldg((const uint32_t*)(P.px + off + 8 * t)); xr[2 * t + 1] = __ldg((const uint32_t*)(P.px + off + 8 * DM + 8 * t)); }
      float acc[28];
      mbar_wait(BAR(B_WO));
#pragma unroll 1
      for (int c = 0; c < 7; c++) {
        mbar_wait(BAR(B_A3 + c), 1);
        if (c == 0) STAMP(10);
        wg_fence();
#pragma unroll
        for (int ks = 0; ks < 4; ks++) wg_ss56<1>(acc, desc(c * (PG / 16), 8 * PG + ks * 32, 16), desc(((c < 4 ? 2 * c : 2 * c + 12) + a) * (PG / 16), ks * 2048, 0), (c | ks) != 0);
      }
      wg_commit();
      mbar_wait(BAR(B_MOD2));
      wg_wait<0>(); keep<28>(acc);
      STAMP(40);
      e_arrive(BAR(B_S3MMA)); e_arrive_remote(mapa(BAR(B_S3MMA2), peer));
#pragma unroll
      for (int t = 0; t < 7; t++) {
        const uint32_t ga = lds32(sb + OFF_GA + a * 112 + j * 4 + t * 16);
        xr[2 * t] = hfma2(ga, pack2(acc[4 * t], acc[4 * t + 1]), xr[2 * t]);
        xr[2 * t + 1] = hfma2(ga, pack2(acc[4 * t + 2], acc[4 * t + 3]), xr[2 * t + 1]);
      }
      bar_sync(1, 256);
      store_rows<7>(xr, PAGE(7 * (cb4 & 1) + a) + w * 2048, g_x1 + (size_t)(64 * h3 + 16 * w) * DM + 112 * c4 + 56 * a, DM, lane);
      const uint32_t p0 = __byte_perm(__shfl_sync(~0u, xr[0], lane & 28), 0, 0x1010), p1 = __byte_perm(__shfl_sync(~0u, xr[1], lane & 28), 0, 0x1010);
      xr[14] = p0; xr[15] = p1;
      float s[4] = {}, q[4] = {};
#pragma unroll
      for (int i = 0; i < 4; i++) {
        uint32_t d[4], e[4];
#pragma unroll
        for (int k = 0; k < 4; k++) { d[k] = hsub2(xr[4 * i + k], (k & 1) ? p1 : p0); e[k] = hmul2(d[k], d[k]); }
        rowsum_mma(s, d);
        rowsum_mma(q, e);
      }
      if (j < 2) {
        const float sd = j ? s[2] : s[0];
        g_st1[(h3 * 8 + 2 * c4 + a) * 64 + r0 + 8 * j] = make_float2(fmaf(bf_lo(j ? p1 : p0), 56.f, sd), fmaf(-sd * (1.f / 56.f), sd, j ? q[2] : q[0]));
      }
      STAMP(41);
      bar_sync(2 + a, 128);
      if (w == 0) e_release(C_X + h3);
    }
    STAMP(11);
    uint32_t zp[28];
    {
      uint32_t A[28][4];
      mbar_wait(BAR(B_MOD2));
      uint32_t rh[2], rl[2], mr[2];
      mbar_wait(BAR(B_A4 + 7 * a));
#pragma unroll
      for (int e = 0; e < 2; e++) {
        float2 q[8];
        float mean = 0.f, m2 = 0.f;
#pragma unroll
        for (int i = 0; i < 8; i++) { q[i] = lds64f(sb + (a ? OFF_RAW1B : OFF_MW) + (r0 + 8 * e) * 8 + i * 512); mean += q[i].x; m2 += q[i].y; }
        mean *= 1.f / 448.f;
#pragma unroll
        for (int i = 0; i < 8; i++) { const float d = fmaf(q[i].x, 1.f / 56.f, -mean); m2 = fmaf(56.f * d, d, m2); }
        const float rstd = rsqrtf(fmaxf(m2, 0.f) * (1.f / 448.f) + 1e-5f);
        rh[e] = pack2(rstd, rstd);
        const float lo = rstd - bf_lo(rh[e]), nm = -mean * rstd;
        rl[e] = pack2(lo, lo); mr[e] = pack2(nm, nm);
      }
      if (a == 1) bar_arrive(4, 256);
#pragma unroll
      for (int c = 0; c < 7; c++) {
        if (c) mbar_wait(BAR(B_A4 + 7 * a + c));
        if (c == 0) STAMP(12);
#pragma unroll
        for (int ks = 0; ks < 4; ks++) ldsm4(A[4 * c + ks], lda[ks] + 7 * a * PG + c * PG);
        if (c == 6) e_arrive(BAR(B_A4RD + a));
        if (c == 1 && a == 0) e_arrive(BAR(B_A4E));
#pragma unroll
        for (int h = 0; h < 2; h++) {
          uint4 cv = lds128(sb + OFF_MOD2 + j * 16 + (2 * c + h) * 64), sv = lds128(sb + OFF_MOD2 + 896 + j * 16 + (2 * c + h) * 64);
          uint32_t cw[4] = {cv.x, cv.y, cv.z, cv.w}, sw[4] = {sv.x, sv.y, sv.z, sv.w};
#pragma unroll
          for (int i = 0; i < 8; i++) {
            uint32_t& x = A[4 * c + 2 * h + (i >> 2)][i & 3];
            x = hfma2(hfma2(x, rh[i & 1], hfma2(x, rl[i & 1], mr[i & 1])), cw[i >> 1], sw[i >> 1]);
          }
        }
      }
      STAMP(49);
#pragma unroll 1
      for (int p = 0; p < 2; p++) {
        float acc[56];
        mbar_wait(BAR(B_Z2W + 3 * p));
        bar_sync(4 + a, 256);
        STAMP(50 + p);
#pragma unroll
        for (int c = 0; c < 7; c++) {
          if (c == 2 || c == 4) { if (p) mbar_wait(BAR(B_Z1W + c / 2)); }
          if (c == 3 || c == 6) { if (!p) mbar_wait(BAR(B_Z2W + c / 3)); }
          wg_fence();
          const int q2 = c < 2 ? 16 + 2 * c : c == 2 ? 15 : c < 6 ? 14 + 2 * c : 0, l2 = c == 2 ? 11 : 1;
          const int q1 = c == 0 ? 4 : c == 1 ? 6 : c == 2 ? 9 : c == 3 ? 11 : c == 4 ? 16 : c == 5 ? 18 : 0, l1 = c == 1 ? 8 : 1;
          const uint32_t d16 = p ? (q1 * (PG / 16)) | (l1 * (PG / 16)) << 16 : (q2 * (PG / 16)) | (l2 * (PG / 16)) << 16;
#pragma unroll
          for (int ks = 0; ks < 4; ks++) wg_rs112<1>(acc, A[4 * c + ks], desc(d16, ks * 2048, 0), (c | ks) != 0);
          wg_commit();
          if (c == 3) { wg_wait<2>(); e_arrive(BAR(B_Z2C + p)); }
          if (c == 5) { wg_wait<2>(); if (p) e_arrive(BAR(B_Z1C + 1)); }
        }
        if (p == 0 || a == 0) bar_arrive(5 - a, 256);
        wg_wait<1>();
        if (p) e_arrive(BAR(B_Z1C + 2));
        wg_wait<0>(); keep<56>(acc);
        if (!p) e_arrive(BAR(B_Z2PASS));
        STAMP(13 + 2 * p);
        float s2[2] = {0.f, 0.f}, q2[2] = {0.f, 0.f};
#pragma unroll
        for (int i = 0; i < 28; i++) {
          const float x = gelu_h(acc[2 * i]), y = gelu_h(acc[2 * i + 1]);
          zp[i] = pack2(x, y);
          s2[i & 1] += x + y;
          q2[i & 1] = fmaf(x, x, fmaf(y, y, q2[i & 1]));
        }
        if (p == 0) {
          const uint32_t sp = PAGE(a ? 7 : 2), stg = sp + (lhi * 8 + lx) * 128 + (((2 * w + ((lane >> 3) & 1)) ^ lx) << 4);
#pragma unroll
          for (int t = 0; t < 7; t++) stsm4t(stg + t * 2048, zp[4 * t], zp[4 * t + 1], zp[4 * t + 2], zp[4 * t + 3]);
          float sv = (j & 1) ? s2[1] : s2[0], qv = (j & 1) ? q2[1] : q2[0];
          sv += __shfl_xor_sync(~0u, (j & 1) ? s2[0] : s2[1], 1); qv += __shfl_xor_sync(~0u, (j & 1) ? q2[0] : q2[1], 1);
          sv += __shfl_xor_sync(~0u, sv, 2); qv += __shfl_xor_sync(~0u, qv, 2);
          if (j < 2) {
            sts64f(sp + 14336 + (r0 + 8 * j) * 8, sv, qv);
            *(uint16_t*)(g_s.zs + (2 * rb + a) * 1024 + c8 * 128 + (((2 * w + j) ^ c8) << 4) + g * 2) = (uint16_t)pack2(sv * (1.f / 896.f), 0.f);
          }
          fence_async_smem();
          bar_sync(2 + a, 128);
          uint8_t* zg = g_z2t + ((size_t)(2 * rb + a) * FH + 112 * c8) * 128 + (tid & 127) * 16;
#pragma unroll
          for (int t = 0; t < 7; t++) stg128(zg + t * 2048, lds128(sp + (tid & 127) * 16 + t * 2048));
          e_arrive(BAR(B_STG + a));
          STAMP(14);
        }
      }
    }
    STAMP(16);
    {
      float acc[116];
      uint32_t A[2][16];
      const size_t row = 128 * rb + 64 * a + r0;
      uint16_t bs0, bs1;
      asm volatile("ld.global.nc.u16 %0, [%2];\nld.global.nc.u16 %1, [%2+16];" : "=h"(bs0), "=h"(bs1) : "l"(P.pbsp + row));
      auto prep = [&](int i, uint32_t* Af) {
        if ((i & 7) == 0) {
          mbar_wait(BAR(B_ST2 + (i >> 3)));
          if (i) {
            e_arrive_remote(mapa(BAR(B_X5FREE), peer));
          }
        }
        const int s = i & 3;
        mbar_wait(BAR(B_S5F + s), (i >> 2) & 1);
        const uint32_t pa = PG * (s == 0 ? 20 : 6 * s - 4) + a * PG;
#pragma unroll
        for (int ks = 0; ks < 4; ks++) ldsm4(Af + 4 * ks, lda[ks] + pa);
#pragma unroll
        for (int h = 0; h < 2; h++) {
          uint4 rv = lds128(sb + OFF_R5 + i * 128 + j * 32 + h * 16);
          uint32_t* p = Af + 8 * h;
          p[0] = hmul2(p[0], rv.x); p[1] = hmul2(p[1], rv.x); p[2] = hmul2(p[2], rv.y); p[3] = hmul2(p[3], rv.y);
          p[4] = hmul2(p[4], rv.z); p[5] = hmul2(p[5], rv.z); p[6] = hmul2(p[6], rv.w); p[7] = hmul2(p[7], rv.w);
        }
      };
      auto mma = [&](int i, const uint32_t* Af) {
        const int s = i & 3;
        wg_fence();
#pragma unroll
        for (int ks = 0; ks < 4; ks++) wg_rs232<0>(acc, Af + 4 * ks, desc((s == 0 ? 22 : 6 * s - 2) * (PG / 16), ks * 32, 16), (i | ks) != 0);
        wg_commit();
        wg_wait<1>();
        if (i > 0) e_arrive(BAR(i < 14 ? B_S5E + ((i - 1) & 3) : B_KPASS - 14 + i));
      };
#pragma unroll 1
      for (int i = 0; i < 16; i += 2) {
        if (i > 0) mma(i - 1, A[1]);
        prep(i, A[0]);
        STAMP(i == 0 ? 17 : 52 + (i >> 1));
        mma(i, A[0]);
        prep(i + 1, A[1]);
      }
      mma(15, A[1]);
      mbar_wait(BAR(B_X5FREE));
      wg_wait<0>(); keep<116>(acc);
      float c0 = quad_sum(acc[112] + acc[113]), c1 = quad_sum(acc[114] + acc[115]);
      e_arrive(BAR(B_QPASS));
      STAMP(18);
      const uint32_t xw = (a ? OFF_XB5_1 : OFF_XB5_0) + w * 3584, xoff = xw + lane * 16;
      const uint32_t rx = mapa(sb + xoff, peer), rbar = mapa(BAR(B_XB5 + a), peer);
#pragma unroll
      for (int q = 0; q < 7; q++) {
        const float* s = acc + 56 + 8 * q;
        st_async4(rx + q * 512, pack2(s[0] - c0, s[1] - c0), pack2(s[2] - c1, s[3] - c1), pack2(s[4] - c0, s[5] - c0), pack2(s[6] - c1, s[7] - c1), rbar);
      }
      c0 = bf_lo(bs0) - c0; c1 = bf_lo(bs1) - c1;
      uint32_t gk[28];
#pragma unroll
      for (int i = 0; i < 28; i++) { const float cc = (i & 1) ? c1 : c0; gk[i] = pack2(acc[2 * i] + cc, acc[2 * i + 1] + cc); }
      STAMP(42);
      mbar_wait(BAR(B_XB5 + a));
      STAMP(43);
#pragma unroll
      for (int q = 0; q < 7; q++) {
        const uint4 v = lds128(sb + xoff + q * 512);
        zp[4 * q] = hmul2(hadd2(gk[4 * q], v.x), zp[4 * q]); zp[4 * q + 1] = hmul2(hadd2(gk[4 * q + 1], v.y), zp[4 * q + 1]);
        zp[4 * q + 2] = hmul2(hadd2(gk[4 * q + 2], v.z), zp[4 * q + 2]); zp[4 * q + 3] = hmul2(hadd2(gk[4 * q + 3], v.w), zp[4 * q + 3]);
      }
      __syncwarp();
      store_rows<14>(zp, sb + xw, g_u + (size_t)(128 * rb + 64 * a + 16 * w) * FH + 112 * c8, FH, lane);
      STAMP(44);
      __syncwarp();
      e_arrive_remote(mapa(BAR(B_X6FREE), peer));
      if (a == 1) e_arrive(BAR(B_XRD));
      bar_sync(2 + a, 128);
      if (w == 0) e_release(C_U + (2 * rb + a) * 2 + (c8 >> 2));
    }
    STAMP(19);
    {
      const size_t off = (size_t)(128 * rb + 64 * a + r0) * DM + 56 * c8 + 2 * j;
      uint32_t xr[14];
#pragma unroll
      for (int t = 0; t < 7; t++) { xr[2 * t] = __ldcg((const uint32_t*)(g_x1 + off + 8 * t)); xr[2 * t + 1] = __ldcg((const uint32_t*)(g_x1 + off + 8 * DM + 8 * t)); }
      float acc[56];
      uint32_t A[2][16];
      auto ld6 = [&](int c, uint32_t* Af) {
        mbar_wait(BAR(B_A4 + 7 * a + c), 1);
#pragma unroll
        for (int ks = 0; ks < 4; ks++) ldsm4(Af + 4 * ks, lda[ks] + (16 + 5 * a + (c < 5 ? c : c - 5)) * PG);
      };
      auto mma6 = [&](int c, const uint32_t* Af) {
        wg_fence();
#pragma unroll
        for (int ks = 0; ks < 4; ks++) wg_rs112<1>(acc, Af + 4 * ks, desc(c * (PG / 8), 2 * PG + ks * 2048, PG), (c | ks) != 0);
        wg_commit();
        wg_wait<1>();
      };
      mbar_wait(BAR(B_B6)); mbar_wait(BAR(B_B6 + 1)); mbar_wait(BAR(B_B6 + 2));
#pragma unroll 1
      for (int c = 0; c < 7; c += 2) {
        if (c) mma6(c - 1, A[1]);
        ld6(c, A[0]);
        if (c == 0) STAMP(45);
        mma6(c, A[0]);
        if (c < 6) ld6(c + 1, A[1]);
        if (c == 0) e_arrive(BAR(B_A6RD + a));
      }
      mbar_wait(BAR(B_X6FREE));
      wg_wait<0>(); keep<56>(acc);
      STAMP(46);
      uint32_t ps[14], pk[14];
#pragma unroll
      for (int i = 0; i < 14; i++) {
        const uint32_t lo = pack2(acc[2 * i], acc[2 * i + 1]), hi = pack2(acc[28 + 2 * i], acc[29 + 2 * i]);
        ps[i] = kh ? lo : hi; pk[i] = kh ? hi : lo;
      }
      const uint32_t xw = a * PG + w * 2048, xoff = xw + lane * 16;
      const uint32_t rx = mapa(sb + xoff, peer), rbar = mapa(BAR(B_XB6 + a), peer);
#pragma unroll
      for (int q = 0; q < 3; q++) st_async4(rx + q * 512, ps[4 * q], ps[4 * q + 1], ps[4 * q + 2], ps[4 * q + 3], rbar);
      st_async2(rx + 1536 - lane * 8, ps[12], ps[13], rbar);
      mbar_wait(BAR(B_XB6 + a));
      STAMP(47);
#pragma unroll
      for (int q = 0; q < 3; q++) { uint4 v = lds128(sb + xoff + q * 512); ps[4 * q] = v.x; ps[4 * q + 1] = v.y; ps[4 * q + 2] = v.z; ps[4 * q + 3] = v.w; }
      { float2 v = lds64f(sb + xw + 1536 + lane * 8); ps[12] = __float_as_uint(v.x); ps[13] = __float_as_uint(v.y); }
#pragma unroll
      for (int t = 0; t < 7; t++) {
        const uint32_t gb = lds32(sb + OFF_GB + j * 4 + t * 16);
        xr[2 * t] = hfma2(gb, hadd2(pk[2 * t], ps[2 * t]), xr[2 * t]);
        xr[2 * t + 1] = hfma2(gb, hadd2(pk[2 * t + 1], ps[2 * t + 1]), xr[2 * t + 1]);
      }
      __syncwarp();
      store_rows<7>(xr, sb + xw, P.out + (size_t)(128 * rb + 64 * a + 16 * w) * DM + 56 * c8, DM, lane);
    }
    if (b == 0 && tid == 0) st_relaxed(&g_epoch, ld_relaxed(&g_epoch) + 1);
  }
}

typedef CUresult (*EncodeFn)(CUtensorMap*, CUtensorMapDataType, cuuint32_t, void*, const cuuint64_t*, const cuuint64_t*, const cuuint32_t*,
                             const cuuint32_t*, CUtensorMapInterleave, CUtensorMapSwizzle, CUtensorMapL2promotion, CUtensorMapFloatOOBfill);

void make_map(EncodeFn enc, CUtensorMap* m, const void* ptr, uint64_t inner, uint64_t outer, uint32_t bi, uint32_t bo,
              CUtensorMapSwizzle sw = CU_TENSOR_MAP_SWIZZLE_128B) {
  cuuint64_t dims[2] = {inner, outer}, strides[1] = {inner * 2};
  cuuint32_t box[2] = {bi, bo}, es[2] = {1, 1};
  enc(m, CU_TENSOR_MAP_DATA_TYPE_BFLOAT16, 2, const_cast<void*>(ptr), dims, strides, box, es, CU_TENSOR_MAP_INTERLEAVE_NONE,
      sw, CU_TENSOR_MAP_L2_PROMOTION_L2_256B, CU_TENSOR_MAP_FLOAT_OOB_FILL_NONE);
}

}

extern "C" void kernel_launch(void* const* d_in, const int* in_sizes, int n_in, void* d_out, int out_size) {
  static EncodeFn enc = nullptr;
  static void *po, *px1, *pu;
  if (!enc) {
    void* fn = nullptr;
    cudaDriverEntryPointQueryResult st;
    cudaGetDriverEntryPoint("cuTensorMapEncodeTiled", &fn, cudaEnableDefault, &st);
    enc = (EncodeFn)fn;
    cudaGetSymbolAddress(&po, g_o);
    cudaGetSymbolAddress(&px1, g_x1);
    cudaGetSymbolAddress(&pu, g_u);
    cudaFuncSetAttribute(fused_kernel, cudaFuncAttributeMaxDynamicSharedMemorySize, SMEM_BYTES);
  }
  typedef const __nv_bfloat16* bp;
  Params P;
  P.px = (bp)d_in[0]; P.pwqkv = (bp)d_in[1]; P.pwo = (bp)d_in[2]; P.pwin = (bp)d_in[4]; P.pwsp = (bp)d_in[5]; P.pbsp = (bp)d_in[6];
  P.pwout = (bp)d_in[7]; P.pc = (bp)d_in[8]; P.pwmod = (bp)d_in[9]; P.out = (__nv_bfloat16*)d_out;
  make_map(enc, &P.wmod, d_in[9], 6 * DM, DM, 8, 224, CU_TENSOR_MAP_SWIZZLE_NONE);
  make_map(enc, &P.wmods, d_in[9], 6 * DM, DM, 224, 224, CU_TENSOR_MAP_SWIZZLE_NONE);
  make_map(enc, &P.x, d_in[0], DM, SEQ, 64, 128);
  make_map(enc, &P.wqkv, d_in[1], 3 * DM, DM, 64, 64);
  make_map(enc, &P.wo64, d_in[2], DM, DM, 56, 64);
  make_map(enc, &P.wo48, d_in[2], DM, DM, 56, 64);
  make_map(enc, &P.win64, d_in[4], 2 * FH, DM, 64, 64);
  make_map(enc, &P.win48, d_in[4], 2 * FH, DM, 48, 64);
  make_map(enc, &P.wsp, d_in[5], SEQ, SEQ, 64, 128);
  make_map(enc, &P.wout64, d_in[7], DM, FH, 64, 64);
  make_map(enc, &P.wout48, d_in[7], DM, FH, 48, 64);
  make_map(enc, &P.o, po, DM, SEQ, 64, 64);
  make_map(enc, &P.x1, px1, DM, SEQ, 64, 64);
  make_map(enc, &P.u, pu, FH, SEQ, 64, 64);
  fused_kernel<<<132, 384, SMEM_BYTES, cudaStreamPerThread>>>(P);
}
```

```cpp
#include <cuda_runtime.h>
#include <cuda_bf16.h>
#include <cuda.h>
#include <stdint.h>

namespace {

constexpr int SEQ = 2048, DM = 448, FH = 896;
constexpr uint32_t PG = 8192;
constexpr uint32_t MISC = 27 * PG;
constexpr uint32_t OFF_MW = MISC;
constexpr uint32_t OFF_MOD1 = MISC + 3072;
constexpr uint32_t OFF_MOD2 = OFF_MOD1 + 2048;
constexpr uint32_t OFF_GA = OFF_MOD2 + 1792;
constexpr uint32_t OFF_GB = OFF_GA + 224;
constexpr uint32_t OFF_R5 = OFF_GB + 112;
constexpr uint32_t OFF_RED = OFF_R5 + 2048;
constexpr uint32_t OFF_BAR = OFF_RED + 256;
constexpr uint32_t SMEM_BYTES = OFF_BAR + 896;
constexpr uint32_t OFF_RAW1B = 14 * PG;
constexpr uint32_t OFF_XB5_0 = 0;
constexpr uint32_t OFF_XB5_1 = 25 * PG + 5120;
static_assert(SMEM_BYTES <= 232448, "smem");

enum : int {
  B_WK = 0, B_WV, B_WQ, B_WO, B_Z2W  , B_Z1W = B_Z2W + 3  , B_B6 = B_Z1W + 3  , B_ST2 = B_B6 + 3  ,
  B_XB5 = B_ST2 + 2  , B_XB6 = B_XB5 + 2  , B_RAW = B_XB6 + 2  , B_X = B_RAW + 2  , B_A3 = B_X, B_A4 = B_A3 + 7  , B_MW = B_A4 + 14, B_S5F  , B_END1 = B_S5F + 4,
  B_CNT2 = 48, B_STGDONE = B_CNT2, B_MOD2,
  B_CNT4 = 60, B_A4RD = B_CNT4  , B_STG = B_A4RD + 2  , B_A6RD = B_STG + 2  , B_KRDY = B_A6RD + 2  ,
  B_A4E = B_KRDY + 4, B_XRD, B_TURN  , B_END4 = B_TURN + 3,
  B_CNT8 = 84, B_XFREE = B_CNT8, B_KPASS, B_VPASS, B_QPASS, B_ATT, B_Z2PASS, B_Z2C, B_Z1C  , B_S5E = B_Z1C + 3  ,
  B_X5FREE = B_S5E + 4, B_X6FREE, B_KALL, B_VALL, B_XFREE2, B_ATT2, B_S3MMA, B_S3MMA2, B_XST, B_END8,
  B_COUNT = 108,
  PH1 = 128
};
static_assert(B_XB5 >= 12 && B_RAW + 2 <= 24 && B_X5FREE >= 96 && B_END1 <= B_CNT2 && B_END4 <= B_CNT8 && B_END8 <= B_COUNT, "barriers");

constexpr int C_K = 0  , C_O = 256, C_X = 288, C_Z = 320, C_U = 352, C_COUNT = 416;

constexpr int CSTR = 64;
constexpr int MODREP = 16;
struct Small {
  uint32_t epoch, pad[31];
  uint32_t mod[MODREP * 2688];
  uint32_t cnt[C_COUNT * CSTR];
  float2 st2[SEQ];
  uint8_t zs[32 * 1024];
  float2 st1[SEQ * 8];
};
__device__ __align__(1024) Small g_s;
#define g_epoch g_s.epoch
#define g_mod g_s.mod
#define g_cnt g_s.cnt
#define g_st1 g_s.st1
#define g_st2 g_s.st2
__device__ __align__(1024) uint8_t g_kv[16 * 8 * 2 * 16384];
__device__ __align__(1024) __nv_bfloat16 g_o[SEQ * DM];
__device__ __align__(1024) __nv_bfloat16 g_x1[SEQ * DM];
__device__ __align__(1024) __nv_bfloat16 g_u[SEQ * FH];
__device__ __align__(1024) uint8_t g_z2t[32 * FH * 128];

struct Params {
  CUtensorMap wmods, wmod, x, wsp, wqkv, wo64, wo48, win64, win48, wout64, wout48;
  const __nv_bfloat16 *px, *pwqkv, *pwo, *pwin, *pwsp, *pbsp, *pwout, *pc, *pwmod;
  __nv_bfloat16* out;
};

__device__ __forceinline__ uint32_t smem_u32(const void* p) { return (uint32_t)__cvta_generic_to_shared(p); }
__device__ __forceinline__ void mbar_init(uint32_t bar, uint32_t cnt) { asm volatile("mbarrier.init.shared::cta.b64 [%0], %1;" ::"r"(bar), "r"(cnt)); }
__device__ __forceinline__ void mbar_arrive(uint32_t bar) { asm volatile("mbarrier.arrive.shared::cta.b64 _, [%0];" ::"r"(bar) : "memory"); }
__device__ __forceinline__ uint32_t mapa(uint32_t addr, uint32_t cta) { uint32_t r; asm volatile("mapa.shared::cluster.u32 %0, %1, %2;" : "=r"(r) : "r"(addr), "r"(cta)); return r; }
__device__ __forceinline__ void mbar_wait2(uint32_t bar, uint32_t par, int& bud) {
  asm volatile("{\n.reg .pred p;\nWLOOP:\nmbarrier.try_wait.parity.shared::cta.b64 p, [%1], %2;\n@p bra WDONE;\n"
               "add.s32 %0, %0, -1;\nsetp.gt.s32 p, %0, 0;\n@p bra WLOOP;\nWDONE:\n}" : "+r"(bud) : "r"(bar), "r"(par) : "memory");
}
__device__ __forceinline__ void bar_sync(int id, int n) { asm volatile("bar.sync %0, %1;" ::"r"(id), "r"(n) : "memory"); }
__device__ __forceinline__ void bar_arrive(int id, int n) { asm volatile("bar.arrive %0, %1;" ::"r"(id), "r"(n) : "memory"); }
__device__ __forceinline__ void fence_async_smem() { asm volatile("fence.proxy.async.shared::cta;" ::: "memory"); }
__device__ __forceinline__ void fence_async_glob() { asm volatile("fence.proxy.async.global;" ::: "memory"); }
#define ELECT(body) "{\n.reg .pred p;\nelect.sync _|p, 0xffffffff;\n@p " body "\n}"
__device__ __forceinline__ void e_expect(uint32_t bar, uint32_t bytes) { asm volatile(ELECT("mbarrier.arrive.expect_tx.shared::cta.b64 _, [%0], %1;") ::"r"(bar), "r"(bytes) : "memory"); }
__device__ __forceinline__ void e_arrive(uint32_t bar) { __syncwarp(); asm volatile(ELECT("mbarrier.arrive.shared::cta.b64 _, [%0];") ::"r"(bar) : "memory"); }
__device__ __forceinline__ void e_arrive_remote(uint32_t rbar) { asm volatile(ELECT("mbarrier.arrive.shared::cluster.b64 _, [%0];") ::"r"(rbar) : "memory"); }
__device__ __forceinline__ void e_tma2d(uint32_t dst, const CUtensorMap* map, int c0, int c1, uint32_t bar) {
  asm volatile(ELECT("cp.async.bulk.tensor.2d.shared::cluster.global.mbarrier::complete_tx::bytes [%0], [%1, {%3, %4}], [%2];")
               ::"r"(dst), "l"(map), "r"(bar), "r"(c0), "r"(c1) : "memory");
}
__device__ __forceinline__ void e_tma2d_mc(uint32_t dst, const CUtensorMap* map, int c0, int c1, uint32_t bar) {
  asm volatile(ELECT("cp.async.bulk.tensor.2d.shared::cluster.global.mbarrier::complete_tx::bytes.multicast::cluster [%0], [%1, {%3, %4}], [%2], %5;")
               ::"r"(dst), "l"(map), "r"(bar), "r"(c0), "r"(c1), "h"((uint16_t)3) : "memory");
}
__device__ __forceinline__ void e_bulk_ld(uint32_t dst, const void* src, uint32_t bytes, uint32_t bar) {
  asm volatile(ELECT("cp.async.bulk.shared::cluster.global.mbarrier::complete_tx::bytes [%0], [%1], %2, [%3];")
               ::"r"(dst), "l"(src), "r"(bytes), "r"(bar) : "memory");
}
__device__ __forceinline__ void e_bulk_ld_mc(uint32_t dst, const void* src, uint32_t bytes, uint32_t bar) {
  asm volatile(ELECT("cp.async.bulk.shared::cluster.global.mbarrier::complete_tx::bytes.multicast::cluster [%0], [%1], %2, [%3], %4;")
               ::"r"(dst), "l"(src), "r"(bytes), "r"(bar), "h"((uint16_t)3) : "memory");
}
__device__ __forceinline__ void e_bulk_st(void* dst, uint32_t src, uint32_t bytes) {
  asm volatile(ELECT("cp.async.bulk.global.shared::cta.bulk_group [%0], [%1], %2;") ::"l"(dst), "r"(src), "r"(bytes) : "memory");
}
__device__ __forceinline__ void bulk_done() {
  asm volatile("cp.async.bulk.commit_group;" ::: "memory");
  asm volatile("cp.async.bulk.wait_group 0;" ::: "memory");
  __syncwarp();
}
__device__ __forceinline__ void l2_prefetch(const void* p, int bytes, int lane) {
#pragma unroll 1
  for (int o = lane * 128; o < bytes; o += 4096) asm volatile("prefetch.global.L2 [%0];" ::"l"((const uint8_t*)p + o) : "memory");
}
__device__ __forceinline__ void prefetch_map(const CUtensorMap* m) { asm volatile("prefetch.tensormap [%0];" ::"l"(m) : "memory"); }
__device__ __forceinline__ uint32_t ld_acquire(const uint32_t* p) { uint32_t v; asm volatile("ld.acquire.gpu.global.u32 %0, [%1];" : "=r"(v) : "l"(p) : "memory"); return v; }
__device__ __forceinline__ uint32_t ld_relaxed(const uint32_t* p) { uint32_t v; asm volatile("ld.relaxed.gpu.global.u32 %0, [%1];" : "=r"(v) : "l"(p) : "memory"); return v; }
__device__ __forceinline__ uint4 ld_relaxed4(const uint32_t* p) {
  uint4 v; asm volatile("ld.relaxed.gpu.global.v4.u32 {%0,%1,%2,%3}, [%4];" : "=r"(v.x), "=r"(v.y), "=r"(v.z), "=r"(v.w) : "l"(p) : "memory"); return v;
}
__device__ __forceinline__ void st_relaxed(uint32_t* p, uint32_t v) { asm volatile("st.relaxed.gpu.global.u32 [%0], %1;" ::"l"(p), "r"(v) : "memory"); }
__device__ __forceinline__ void e_release(int c) { __syncwarp(); asm volatile(ELECT("red.release.gpu.global.add.u32 [%0], 1;") ::"l"(&g_cnt[c * CSTR]) : "memory"); }
__device__ __forceinline__ void e_publish(int c) { bulk_done(); fence_async_glob(); e_release(c); }
__device__ __forceinline__ bool reached(int c, uint32_t target) { return (int)(ld_acquire(&g_cnt[c * CSTR]) - target) >= 0; }
__device__ __forceinline__ void ldsm4(uint32_t* r, uint32_t addr) {
  asm volatile("ldmatrix.sync.aligned.m8n8.x4.shared.b16 {%0,%1,%2,%3}, [%4];" : "=r"(r[0]), "=r"(r[1]), "=r"(r[2]), "=r"(r[3]) : "r"(addr) : "memory");
}
__device__ __forceinline__ void stsm4(uint32_t addr, uint32_t r0, uint32_t r1, uint32_t r2, uint32_t r3) {
  asm volatile("stmatrix.sync.aligned.m8n8.x4.shared.b16 [%0], {%1,%2,%3,%4};" ::"r"(addr), "r"(r0), "r"(r1), "r"(r2), "r"(r3) : "memory");
}
__device__ __forceinline__ void stsm2(uint32_t addr, uint32_t r0, uint32_t r1) {
  asm volatile("stmatrix.sync.aligned.m8n8.x2.shared.b16 [%0], {%1,%2};" ::"r"(addr), "r"(r0), "r"(r1) : "memory");
}
__device__ __forceinline__ void stsm4t(uint32_t addr, uint32_t r0, uint32_t r1, uint32_t r2, uint32_t r3) {
  asm volatile("stmatrix.sync.aligned.m8n8.x4.trans.shared.b16 [%0], {%1,%2,%3,%4};" ::"r"(addr), "r"(r0), "r"(r1), "r"(r2), "r"(r3) : "memory");
}
__device__ __forceinline__ uint4 lds128(uint32_t addr) {
  uint4 v; asm volatile("ld.shared.v4.u32 {%0,%1,%2,%3}, [%4];" : "=r"(v.x), "=r"(v.y), "=r"(v.z), "=r"(v.w) : "r"(addr) : "memory"); return v;
}
__device__ __forceinline__ float2 lds64f(uint32_t addr) {
  float2 v; asm volatile("ld.shared.v2.f32 {%0,%1}, [%2];" : "=f"(v.x), "=f"(v.y) : "r"(addr) : "memory"); return v;
}
__device__ __forceinline__ void sts32(uint32_t addr, uint32_t v) { asm volatile("st.shared.u32 [%0], %1;" ::"r"(addr), "r"(v) : "memory"); }
__device__ __forceinline__ void sts32f(uint32_t addr, float v) { asm volatile("st.shared.f32 [%0], %1;" ::"r"(addr), "f"(v) : "memory"); }
__device__ __forceinline__ uint32_t lds32(uint32_t addr) { uint32_t v; asm volatile("ld.shared.u32 %0, [%1];" : "=r"(v) : "r"(addr) : "memory"); return v; }
__device__ __forceinline__ float lds32f(uint32_t addr) { float v; asm volatile("ld.shared.f32 %0, [%1];" : "=f"(v) : "r"(addr) : "memory"); return v; }
__device__ __forceinline__ void sts128(uint32_t addr, uint4 v) { asm volatile("st.shared.v4.u32 [%0], {%1,%2,%3,%4};" ::"r"(addr), "r"(v.x), "r"(v.y), "r"(v.z), "r"(v.w) : "memory"); }
__device__ __forceinline__ void st_async4(uint32_t raddr, uint32_t a, uint32_t b, uint32_t c, uint32_t d, uint32_t rbar) {
  asm volatile("st.async.shared::cluster.mbarrier::complete_tx::bytes.v4.b32 [%0], {%1,%2,%3,%4}, [%5];" ::"r"(raddr), "r"(a), "r"(b), "r"(c), "r"(d), "r"(rbar) : "memory");
}
__device__ __forceinline__ void st_async2(uint32_t raddr, uint32_t a, uint32_t b, uint32_t rbar) {
  asm volatile("st.async.shared::cluster.mbarrier::complete_tx::bytes.v2.b32 [%0], {%1,%2}, [%3];" ::"r"(raddr), "r"(a), "r"(b), "r"(rbar) : "memory");
}
__device__ __forceinline__ uint32_t pack2(float lo, float hi) { uint32_t r; asm("cvt.rn.bf16x2.f32 %0, %1, %2;" : "=r"(r) : "f"(hi), "f"(lo)); return r; }
__device__ __forceinline__ float bf_lo(uint32_t w) { return __uint_as_float(w << 16); }
__device__ __forceinline__ float bf_hi(uint32_t w) { return __uint_as_float(w & 0xFFFF0000u); }
__device__ __forceinline__ uint32_t hfma2(uint32_t a, uint32_t b, uint32_t c) { uint32_t r; asm("fma.rn.bf16x2 %0, %1, %2, %3;" : "=r"(r) : "r"(a), "r"(b), "r"(c)); return r; }
__device__ __forceinline__ uint32_t hmul2(uint32_t a, uint32_t b) { uint32_t r; asm("mul.rn.bf16x2 %0, %1, %2;" : "=r"(r) : "r"(a), "r"(b)); return r; }
__device__ __forceinline__ uint32_t hsub2(uint32_t a, uint32_t b) { uint32_t r; asm("sub.rn.bf16x2 %0, %1, %2;" : "=r"(r) : "r"(a), "r"(b)); return r; }
__device__ __forceinline__ float ex2v(float x) { float r; asm volatile("ex2.approx.ftz.f32 %0, %1;" : "=f"(r) : "f"(x)); return r; }
__device__ __forceinline__ void stg128(void* p, uint4 v) { asm volatile("st.global.v4.u32 [%0], {%1,%2,%3,%4};" ::"l"(p), "r"(v.x), "r"(v.y), "r"(v.z), "r"(v.w) : "memory"); }
__device__ __forceinline__ uint32_t hadd2(uint32_t a, uint32_t b) { uint32_t r; asm("add.rn.bf16x2 %0, %1, %2;" : "=r"(r) : "r"(a), "r"(b)); return r; }
__device__ __forceinline__ float ex2(float x) { float r; asm("ex2.approx.ftz.f32 %0, %1;" : "=f"(r) : "f"(x)); return r; }
__device__ __forceinline__ float gelu_h(float y) {
  float u = y * fmaf(8.f * 0.0356774081f, y * y, 2.f * 0.7978845608f), t;
  asm("tanh.approx.f32 %0, %1;" : "=f"(t) : "f"(u));
  return fmaf(y, t, y);
}
__device__ __forceinline__ float quad_sum(float v) { v += __shfl_xor_sync(~0u, v, 1); v += __shfl_xor_sync(~0u, v, 2); return v; }
__device__ __forceinline__ float quad_max(float v) { v = fmaxf(v, __shfl_xor_sync(~0u, v, 1)); v = fmaxf(v, __shfl_xor_sync(~0u, v, 2)); return v; }
__device__ __forceinline__ void rowsum_mma(float* c, const uint32_t* a) {
  asm volatile("mma.sync.aligned.m16n8k16.row.col.f32.bf16.bf16.f32 {%0,%1,%2,%3}, {%4,%5,%6,%7}, {%8,%8}, {%0,%1,%2,%3};"
               : "+f"(c[0]), "+f"(c[1]), "+f"(c[2]), "+f"(c[3]) : "r"(a[0]), "r"(a[1]), "r"(a[2]), "r"(a[3]), "r"(0x3F803F80u));
}
__device__ __forceinline__ void wg_fence() { asm volatile("wgmma.fence.sync.aligned;" ::: "memory"); }
__device__ __forceinline__ void wg_commit() { asm volatile("wgmma.commit_group.sync.aligned;" ::: "memory"); }
template <int N> __device__ __forceinline__ void wg_wait() { asm volatile("wgmma.wait_group.sync.aligned %0;" ::"n"(N) : "memory"); }
constexpr uint32_t SMEM0 = 1024;
__device__ __forceinline__ uint64_t desc(uint32_t rt16, uint32_t off, uint32_t lbo) {
  return (uint64_t)(rt16 + (((SMEM0 + off) >> 4) | ((lbo >> 4) << 16))) | ((uint64_t)0x40000040u << 32);
}
template <int N> __device__ __forceinline__ void keep(float* d) {
#pragma unroll
  for (int i = 0; i < N; i++) asm volatile("" : "+f"(d[i]));
}

template <int TB> __device__ __forceinline__ void wg_rs32(float* d, const uint32_t* a, uint64_t db, int sd) {
  asm volatile("{\n.reg .pred p;\nsetp.ne.b32 p, %21, 0;\n"
    "wgmma.mma_async.sync.aligned.m64n32k16.f32.bf16.bf16 {%0, %1, %2, %3, %4, %5, %6, %7, %8, %9, %10, %11, %12, %13, %14, %15}, {%16, %17, %18, %19}, %20, p, 1, 1, %22;\n}"
    : "+f"(d[0]), "+f"(d[1]), "+f"(d[2]), "+f"(d[3]), "+f"(d[4]), "+f"(d[5]), "+f"(d[6]), "+f"(d[7]), "+f"(d[8]), "+f"(d[9]), "+f"(d[10]), "+f"(d[11]), "+f"(d[12]), "+f"(d[13]), "+f"(d[14]), "+f"(d[15])
    : "r"(a[0]), "r"(a[1]), "r"(a[2]), "r"(a[3]), "l"(db), "r"(sd), "n"(TB));
}
template <int TB> __device__ __forceinline__ void wg_rs56(float* d, const uint32_t* a, uint64_t db, int sd) {
  asm volatile("{\n.reg .pred p;\nsetp.ne.b32 p, %33, 0;\n"
    "wgmma.mma_async.sync.aligned.m64n56k16.f32.bf16.bf16 {%0, %1, %2, %3, %4, %5, %6, %7, %8, %9, %10, %11, %12, %13, %14, %15, %16, %17, %18, %19, %20, %21, %22, %23, %24, %25, %26, %27}, {%28, %29, %30, %31}, %32, p, 1, 1, %34;\n}"
    : "+f"(d[0]), "+f"(d[1]), "+f"(d[2]), "+f"(d[3]), "+f"(d[4]), "+f"(d[5]), "+f"(d[6]), "+f"(d[7]), "+f"(d[8]), "+f"(d[9]), "+f"(d[10]), "+f"(d[11]), "+f"(d[12]), "+f"(d[13]), "+f"(d[14]), "+f"(d[15]), "+f"(d[16]), "+f"(d[17]), "+f"(d[18]), "+f"(d[19]), "+f"(d[20]), "+f"(d[21]), "+f"(d[22]), "+f"(d[23]), "+f"(d[24]), "+f"(d[25]), "+f"(d[26]), "+f"(d[27])
    : "r"(a[0]), "r"(a[1]), "r"(a[2]), "r"(a[3]), "l"(db), "r"(sd), "n"(TB));
}
template <int TB> __device__ __forceinline__ void wg_rs64(float* d, const uint32_t* a, uint64_t db, int sd) {
  asm volatile("{\n.reg .pred p;\nsetp.ne.b32 p, %37, 0;\n"
    "wgmma.mma_async.sync.aligned.m64n64k16.f32.bf16.bf16 {%0, %1, %2, %3, %4, %5, %6, %7, %8, %9, %10, %11, %12, %13, %14, %15, %16, %17, %18, %19, %20, %21, %22, %23, %24, %25, %26, %27, %28, %29, %30, %31}, {%32, %33, %34, %35}, %36, p, 1, 1, %38;\n}"
    : "+f"(d[0]), "+f"(d[1]), "+f"(d[2]), "+f"(d[3]), "+f"(d[4]), "+f"(d[5]), "+f"(d[6]), "+f"(d[7]), "+f"(d[8]), "+f"(d[9]), "+f"(d[10]), "+f"(d[11]), "+f"(d[12]), "+f"(d[13]), "+f"(d[14]), "+f"(d[15]), "+f"(d[16]), "+f"(d[17]), "+f"(d[18]), "+f"(d[19]), "+f"(d[20]), "+f"(d[21]), "+f"(d[22]), "+f"(d[23]), "+f"(d[24]), "+f"(d[25]), "+f"(d[26]), "+f"(d[27]), "+f"(d[28]), "+f"(d[29]), "+f"(d[30]), "+f"(d[31])
    : "r"(a[0]), "r"(a[1]), "r"(a[2]), "r"(a[3]), "l"(db), "r"(sd), "n"(TB));
}
template <int TB> __device__ __forceinline__ void wg_rs112(float* d, const uint32_t* a, uint64_t db, int sd) {
  asm volatile("{\n.reg .pred p;\nsetp.ne.b32 p, %61, 0;\n"
    "wgmma.mma_async.sync.aligned.m64n112k16.f32.bf16.bf16 {%0, %1, %2, %3, %4, %5, %6, %7, %8, %9, %10, %11, %12, %13, %14, %15, %16, %17, %18, %19, %20, %21, %22, %23, %24, %25, %26, %27, %28, %29, %30, %31, %32, %33, %34, %35, %36, %37, %38, %39, %40, %41, %42, %43, %44, %45, %46, %47, %48, %49, %50, %51, %52, %53, %54, %55}, {%56, %57, %58, %59}, %60, p, 1, 1, %62;\n}"
    : "+f"(d[0]), "+f"(d[1]), "+f"(d[2]), "+f"(d[3]), "+f"(d[4]), "+f"(d[5]), "+f"(d[6]), "+f"(d[7]), "+f"(d[8]), "+f"(d[9]), "+f"(d[10]), "+f"(d[11]), "+f"(d[12]), "+f"(d[13]), "+f"(d[14]), "+f"(d[15]), "+f"(d[16]), "+f"(d[17]), "+f"(d[18]), "+f"(d[19]), "+f"(d[20]), "+f"(d[21]), "+f"(d[22]), "+f"(d[23]), "+f"(d[24]), "+f"(d[25]), "+f"(d[26]), "+f"(d[27]), "+f"(d[28]), "+f"(d[29]), "+f"(d[30]), "+f"(d[31]), "+f"(d[32]), "+f"(d[33]), "+f"(d[34]), "+f"(d[35]), "+f"(d[36]), "+f"(d[37]), "+f"(d[38]), "+f"(d[39]), "+f"(d[40]), "+f"(d[41]), "+f"(d[42]), "+f"(d[43]), "+f"(d[44]), "+f"(d[45]), "+f"(d[46]), "+f"(d[47]), "+f"(d[48]), "+f"(d[49]), "+f"(d[50]), "+f"(d[51]), "+f"(d[52]), "+f"(d[53]), "+f"(d[54]), "+f"(d[55])
    : "r"(a[0]), "r"(a[1]), "r"(a[2]), "r"(a[3]), "l"(db), "r"(sd), "n"(TB));
}
template <int TB> __device__ __forceinline__ void wg_rs192(float* d, const uint32_t* a, uint64_t db, int sd) {
  asm volatile("{\n.reg .pred p;\nsetp.ne.b32 p, %101, 0;\n"
    "wgmma.mma_async.sync.aligned.m64n192k16.f32.bf16.bf16 {%0, %1, %2, %3, %4, %5, %6, %7, %8, %9, %10, %11, %12, %13, %14, %15, %16, %17, %18, %19, %20, %21, %22, %23, %24, %25, %26, %27, %28, %29, %30, %31, %32, %33, %34, %35, %36, %37, %38, %39, %40, %41, %42, %43, %44, %45, %46, %47, %48, %49, %50, %51, %52, %53, %54, %55, %56, %57, %58, %59, %60, %61, %62, %63, %64, %65, %66, %67, %68, %69, %70, %71, %72, %73, %74, %75, %76, %77, %78, %79, %80, %81, %82, %83, %84, %85, %86, %87, %88, %89, %90, %91, %92, %93, %94, %95}, {%96, %97, %98, %99}, %100, p, 1, 1, %102;\n}"
    : "+f"(d[0]), "+f"(d[1]), "+f"(d[2]), "+f"(d[3]), "+f"(d[4]), "+f"(d[5]), "+f"(d[6]), "+f"(d[7]), "+f"(d[8]), "+f"(d[9]), "+f"(d[10]), "+f"(d[11]), "+f"(d[12]), "+f"(d[13]), "+f"(d[14]), "+f"(d[15]), "+f"(d[16]), "+f"(d[17]), "+f"(d[18]), "+f"(d[19]), "+f"(d[20]), "+f"(d[21]), "+f"(d[22]), "+f"(d[23]), "+f"(d[24]), "+f"(d[25]), "+f"(d[26]), "+f"(d[27]), "+f"(d[28]), "+f"(d[29]), "+f"(d[30]), "+f"(d[31]), "+f"(d[32]), "+f"(d[33]), "+f"(d[34]), "+f"(d[35]), "+f"(d[36]), "+f"(d[37]), "+f"(d[38]), "+f"(d[39]), "+f"(d[40]), "+f"(d[41]), "+f"(d[42]), "+f"(d[43]), "+f"(d[44]), "+f"(d[45]), "+f"(d[46]), "+f"(d[47]), "+f"(d[48]), "+f"(d[49]), "+f"(d[50]), "+f"(d[51]), "+f"(d[52]), "+f"(d[53]), "+f"(d[54]), "+f"(d[55]), "+f"(d[56]), "+f"(d[57]), "+f"(d[58]), "+f"(d[59]), "+f"(d[60]), "+f"(d[61]), "+f"(d[62]), "+f"(d[63]), "+f"(d[64]), "+f"(d[65]), "+f"(d[66]), "+f"(d[67]), "+f"(d[68]), "+f"(d[69]), "+f"(d[70]), "+f"(d[71]), "+f"(d[72]), "+f"(d[73]), "+f"(d[74]), "+f"(d[75]), "+f"(d[76]), "+f"(d[77]), "+f"(d[78]), "+f"(d[79]), "+f"(d[80]), "+f"(d[81]), "+f"(d[82]), "+f"(d[83]), "+f"(d[84]), "+f"(d[85]), "+f"(d[86]), "+f"(d[87]), "+f"(d[88]), "+f"(d[89]), "+f"(d[90]), "+f"(d[91]), "+f"(d[92]), "+f"(d[93]), "+f"(d[94]), "+f"(d[95])
    : "r"(a[0]), "r"(a[1]), "r"(a[2]), "r"(a[3]), "l"(db), "r"(sd), "n"(TB));
}
template <int TB> __device__ __forceinline__ void wg_rs232(float* d, const uint32_t* a, uint64_t db, int sd) {
  asm volatile("{\n.reg .pred p;\nsetp.ne.b32 p, %121, 0;\n"
    "wgmma.mma_async.sync.aligned.m64n232k16.f32.bf16.bf16 {%0, %1, %2, %3, %4, %5, %6, %7, %8, %9, %10, %11, %12, %13, %14, %15, %16, %17, %18, %19, %20, %21, %22, %23, %24, %25, %26, %27, %28, %29, %30, %31, %32, %33, %34, %35, %36, %37, %38, %39, %40, %41, %42, %43, %44, %45, %46, %47, %48, %49, %50, %51, %52, %53, %54, %55, %56, %57, %58, %59, %60, %61, %62, %63, %64, %65, %66, %67, %68, %69, %70, %71, %72, %73, %74, %75, %76, %77, %78, %79, %80, %81, %82, %83, %84, %85, %86, %87, %88, %89, %90, %91, %92, %93, %94, %95, %96, %97, %98, %99, %100, %101, %102, %103, %104, %105, %106, %107, %108, %109, %110, %111, %112, %113, %114, %115}, {%116, %117, %118, %119}, %120, p, 1, 1, %122;\n}"
    : "+f"(d[0]), "+f"(d[1]), "+f"(d[2]), "+f"(d[3]), "+f"(d[4]), "+f"(d[5]), "+f"(d[6]), "+f"(d[7]), "+f"(d[8]), "+f"(d[9]), "+f"(d[10]), "+f"(d[11]), "+f"(d[12]), "+f"(d[13]), "+f"(d[14]), "+f"(d[15]), "+f"(d[16]), "+f"(d[17]), "+f"(d[18]), "+f"(d[19]), "+f"(d[20]), "+f"(d[21]), "+f"(d[22]), "+f"(d[23]), "+f"(d[24]), "+f"(d[25]), "+f"(d[26]), "+f"(d[27]), "+f"(d[28]), "+f"(d[29]), "+f"(d[30]), "+f"(d[31]), "+f"(d[32]), "+f"(d[33]), "+f"(d[34]), "+f"(d[35]), "+f"(d[36]), "+f"(d[37]), "+f"(d[38]), "+f"(d[39]), "+f"(d[40]), "+f"(d[41]), "+f"(d[42]), "+f"(d[43]), "+f"(d[44]), "+f"(d[45]), "+f"(d[46]), "+f"(d[47]), "+f"(d[48]), "+f"(d[49]), "+f"(d[50]), "+f"(d[51]), "+f"(d[52]), "+f"(d[53]), "+f"(d[54]), "+f"(d[55]), "+f"(d[56]), "+f"(d[57]), "+f"(d[58]), "+f"(d[59]), "+f"(d[60]), "+f"(d[61]), "+f"(d[62]), "+f"(d[63]), "+f"(d[64]), "+f"(d[65]), "+f"(d[66]), "+f"(d[67]), "+f"(d[68]), "+f"(d[69]), "+f"(d[70]), "+f"(d[71]), "+f"(d[72]), "+f"(d[73]), "+f"(d[74]), "+f"(d[75]), "+f"(d[76]), "+f"(d[77]), "+f"(d[78]), "+f"(d[79]), "+f"(d[80]), "+f"(d[81]), "+f"(d[82]), "+f"(d[83]), "+f"(d[84]), "+f"(d[85]), "+f"(d[86]), "+f"(d[87]), "+f"(d[88]), "+f"(d[89]), "+f"(d[90]), "+f"(d[91]), "+f"(d[92]), "+f"(d[93]), "+f"(d[94]), "+f"(d[95]), "+f"(d[96]), "+f"(d[97]), "+f"(d[98]), "+f"(d[99]), "+f"(d[100]), "+f"(d[101]), "+f"(d[102]), "+f"(d[103]), "+f"(d[104]), "+f"(d[105]), "+f"(d[106]), "+f"(d[107]), "+f"(d[108]), "+f"(d[109]), "+f"(d[110]), "+f"(d[111]), "+f"(d[112]), "+f"(d[113]), "+f"(d[114]), "+f"(d[115])
    : "r"(a[0]), "r"(a[1]), "r"(a[2]), "r"(a[3]), "l"(db), "r"(sd), "n"(TB));
}
template <int TB> __device__ __forceinline__ void wg_ss56(float* d, uint64_t da, uint64_t db, int sd) {
  asm volatile("{\n.reg .pred p;\nsetp.ne.b32 p, %30, 0;\n"
    "wgmma.mma_async.sync.aligned.m64n56k16.f32.bf16.bf16 {%0, %1, %2, %3, %4, %5, %6, %7, %8, %9, %10, %11, %12, %13, %14, %15, %16, %17, %18, %19, %20, %21, %22, %23, %24, %25, %26, %27}, %28, %29, p, 1, 1, 0, %31;\n}"
    : "+f"(d[0]), "+f"(d[1]), "+f"(d[2]), "+f"(d[3]), "+f"(d[4]), "+f"(d[5]), "+f"(d[6]), "+f"(d[7]), "+f"(d[8]), "+f"(d[9]), "+f"(d[10]), "+f"(d[11]), "+f"(d[12]), "+f"(d[13]), "+f"(d[14]), "+f"(d[15]), "+f"(d[16]), "+f"(d[17]), "+f"(d[18]), "+f"(d[19]), "+f"(d[20]), "+f"(d[21]), "+f"(d[22]), "+f"(d[23]), "+f"(d[24]), "+f"(d[25]), "+f"(d[26]), "+f"(d[27])
    : "l"(da), "l"(db), "r"(sd), "n"(TB));
}


__device__ __forceinline__ int perm448(int k) { return (k >> 5) * 32 + ((k & 7) >> 1) * 8 + ((k >> 4) & 1) * 4 + ((k >> 3) & 1) * 2 + (k & 1); }
__device__ __forceinline__ int perm64(int k) { return ((k & 7) >> 1) * 16 + (k >> 4) * 4 + ((k >> 3) & 1) * 2 + (k & 1); }

__device__ __forceinline__ float rcp(float x) { float r; asm("rcp.approx.ftz.f32 %0, %1;" : "=f"(r) : "f"(x)); return r; }
__device__ __forceinline__ float silu_bf(float c) { return bf_lo(pack2(c * rcp(1.f + ex2(-1.4426950408889634f * c)), 0.f)); }
__device__ __forceinline__ void fma8(float* acc, uint4 w, float s) {
  acc[0] = fmaf(bf_lo(w.x), s, acc[0]); acc[1] = fmaf(bf_hi(w.x), s, acc[1]);
  acc[2] = fmaf(bf_lo(w.y), s, acc[2]); acc[3] = fmaf(bf_hi(w.y), s, acc[3]);
  acc[4] = fmaf(bf_lo(w.z), s, acc[4]); acc[5] = fmaf(bf_hi(w.z), s, acc[5]);
  acc[6] = fmaf(bf_lo(w.w), s, acc[6]); acc[7] = fmaf(bf_hi(w.w), s, acc[7]);
}
__device__ __forceinline__ float warp_red8(float* v, int lane) {
  bool b4 = lane & 16, b3 = lane & 8, b2 = lane & 4;
  float t[4];
#pragma unroll
  for (int i = 0; i < 4; i++) { float keepv = b4 ? v[i + 4] : v[i], send = b4 ? v[i] : v[i + 4]; t[i] = keepv + __shfl_xor_sync(~0u, send, 16); }
  float u[2];
#pragma unroll
  for (int i = 0; i < 2; i++) { float keepv = b3 ? t[i + 2] : t[i], send = b3 ? t[i] : t[i + 2]; u[i] = keepv + __shfl_xor_sync(~0u, send, 8); }
  float keepv = b2 ? u[1] : u[0], send = b2 ? u[0] : u[1];
  float r = keepv + __shfl_xor_sync(~0u, send, 4);
  r += __shfl_xor_sync(~0u, r, 2);
  r += __shfl_xor_sync(~0u, r, 1);
  return r;
}

template <int NT> __device__ __forceinline__ void stage_rows(const uint32_t* w, uint32_t stg, int lane) {
  const uint32_t sa = stg + (lane & 15) * (NT * 16) + (lane >> 4) * 16;
#pragma unroll
  for (int t = 0; t + 1 < NT; t += 2) stsm4(sa + t * 16, w[2 * t], w[2 * t + 1], w[2 * t + 2], w[2 * t + 3]);
  if (NT & 1) stsm2(sa + (NT - 1) * 16, w[2 * NT - 2], w[2 * NT - 1]);
}
template <int NT> __device__ __forceinline__ void store_cm(const uint32_t* w, __nv_bfloat16* p) {
#pragma unroll
  for (int t = 0; t < NT; t++) { *(uint32_t*)(p + t * 512) = w[2 * t]; *(uint32_t*)(p + t * 512 + 64) = w[2 * t + 1]; }
}
template <int NT> __device__ __forceinline__ void store_rows(const uint32_t* w, uint32_t stg, __nv_bfloat16* gp, int pitch, int lane) {
  stage_rows<NT>(w, stg, lane);
  __syncwarp();
  {
    const int r = (lane * 37) >> 8, c = lane - 7 * r;
    gp += r * pitch + c * 8;
    if (lane < 28) {
#pragma unroll
      for (int k = 0; k < 4; k++) stg128(gp + 4 * k * pitch, lds128(stg + lane * 16 + k * 448));
    }
  }
}
__device__ __forceinline__ int st2pos(int h) { return ((h >> 4) * 16 + (h & 1) * 8 + ((h >> 1) & 7)) * 64; }
__device__ __forceinline__ uint32_t mod_bad(uint4 v, uint32_t tag) { return (v.x ^ tag) | (v.y ^ tag) | (v.z ^ tag) | (v.w ^ tag); }
__device__ __forceinline__ void put_mod4(uint32_t base, int i, uint4 v, uint32_t s2) {
  const bool isc = i >= 112;
  const float one = isc ? 1.f : 0.f;
  const int k = (isc ? i - 112 : i) * 4;
  base += (isc ? 0 : 896) + perm448(k) * 2;
  sts32(base, hmul2(pack2(bf_lo(v.x) + one, bf_lo(v.y) + one), s2));
  sts32(base + 16, hmul2(pack2(bf_lo(v.z) + one, bf_lo(v.w) + one), s2));
}

__host__ __device__ constexpr uint32_t bar_count(int i) { return i >= B_CNT8 ? 8 : i >= B_CNT4 ? 4 : i >= B_CNT2 ? 2 : 1; }
constexpr uint32_t WE(int wait, int p0, int p1, int full, int c, int type, int add, int n) {
  return (uint32_t)wait | p0 << 8 | p1 << 13 | full << 18 | c << 22 | type << 25 | add << 27 | (uint32_t)n << 29;
}
__constant__ uint32_t c_wprog[28] = {
  WE(B_VALL, 20, 21, B_WO, 4, 1, 0, 7), WE(0, 22, 23, B_WO, 5, 1, 0, 0), WE(0, 24, 25, B_WO, 6, 1, 0, 0),
  WE(B_QPASS, 0, 1, B_WO, 0, 1, 0, 0), WE(0, 2, 3, B_WO, 1, 1, 0, 0), WE(0, 4, 5, B_WO, 2, 1, 0, 0), WE(0, 6, 7, B_WO, 3, 1, 0, 0),
  WE(PH1 + B_A3 + 6, 16, 17, B_Z2W, 0, 2, 2, 3), WE(0, 18, 19, B_Z2W, 1, 2, 2, 0), WE(B_XST, 15, 26, B_Z2W, 2, 2, 2, 0),
  WE(B_A4 + 5, 20, 21, B_Z2W + 1, 3, 2, 2, 3), WE(0, 22, 23, B_Z2W + 1, 4, 2, 2, 0), WE(0, 24, 25, B_Z2W + 1, 5, 2, 2, 0),
  WE(B_A4E, 0, 1, B_Z2W + 2, 6, 2, 2, 1),
  WE(B_A4RD, 4, 5, B_Z1W, 0, 2, 0, 2), WE(B_A4RD + 1, 6, 14, B_Z1W, 1, 2, 0, 0),
  WE(0, 9, 10, B_Z1W + 1, 2, 2, 0, 2), WE(0, 11, 12, B_Z1W + 1, 3, 2, 0, 0),
  WE(B_Z2C, 16, 17, B_Z1W + 2, 4, 2, 0, 3), WE(0, 18, 19, B_Z1W + 2, 5, 2, 0, 0), WE(B_Z2PASS, 0, 1, B_Z1W + 2, 6, 2, 0, 0),
  WE(PH1 + B_KPASS, 2, 3, B_B6, 0, 3, 0, 3), WE(0, 4, 5, B_B6, 1, 3, 0, 0), WE(0, 6, 7, B_B6, 2, 3, 0, 0),
  WE(PH1 + B_VPASS, 8, 9, B_B6 + 1, 3, 3, 0, 3), WE(0, 10, 11, B_B6 + 1, 4, 3, 0, 0), WE(0, 12, 13, B_B6 + 1, 5, 3, 0, 0),
  WE(PH1 + B_QPASS, 14, 15, B_B6 + 2, 6, 3, 0, 1)};

__global__ void __cluster_dims__(2, 1, 1) __launch_bounds__(384, 1) fused_kernel(const __grid_constant__ Params P) {
  extern __shared__ __align__(1024) uint8_t smem_raw[];
  const uint32_t sb = smem_u32(smem_raw);
  const int tid = threadIdx.x, lane = tid & 31, warp = __shfl_sync(~0u, tid >> 5, 0);
  const int b = blockIdx.x, rb = b >> 3, c8 = b & 7, cb4 = c8 >> 1, kh = c8 & 1;
  const int h3 = 2 * rb + (cb4 & 1), c4 = 2 * (cb4 >> 1) + kh;
  const int rb1 = 2 * (b >> 4) + kh, j1 = (b >> 1) & 7, b1 = rb1 * 8 + j1;
  const uint32_t peer = kh ^ 1;
  int bud = 1 << 20;
  auto BAR = [&](int i) { return sb + OFF_BAR + 8u * i; };
  auto PAGE = [&](int i) { return sb + PG * i; };
  auto mbar_wait = [&](uint32_t bar, uint32_t par = 0) { mbar_wait2(bar, par, bud); };
  auto poll = [&](int c, uint32_t target) { while (!__all_sync(~0u, reached(c, target)) && --bud > 0) {} fence_async_glob(); };

  if (blockIdx.x >= 128) {
    float* tab = (float*)(smem_raw + 200704);
    const int rg = min(tid / 56, 5), cg = tid - 56 * (tid / 56), col0 = 448 * (b - 126);
    if (tid == 0) mbar_init(BAR(0), 1);
    __syncthreads();
    const uint32_t tg = (ld_relaxed(&g_epoch) + 1) << 16;
    float acc[8] = {0, 0, 0, 0, 0, 0, 0, 0};
#pragma unroll 1
    for (int h = 0; h < 2; h++) {
      if (warp == 0) {
        e_expect(BAR(0), 200704);
        e_tma2d(sb, &P.wmods, col0, 224 * h, BAR(0));
        e_tma2d(sb + 100352, &P.wmods, col0 + 224, 224 * h, BAR(0));
      }
      if (tid < 224) tab[tid] = silu_bf(bf_lo(__ldg((const uint16_t*)P.pc + 224 * h + tid)));
      __syncthreads();
      mbar_wait(BAR(0), h);
#pragma unroll 2
      for (int k = rg; k < 224; k += 6) fma8(acc, lds128(sb + (cg >= 28 ? 100352 - 448 : 0) + k * 448 + cg * 16), tab[k]);
      __syncthreads();
    }
    if (tid < 336) {
#pragma unroll
      for (int i = 0; i < 8; i++) tab[512 + rg * 448 + cg * 8 + i] = acc[i];
    }
    __syncthreads();
    for (int c = tid; c < 448; c += 384) {
      float v = 0.f;
#pragma unroll
      for (int i = 0; i < 6; i++) v += tab[512 + i * 448 + c];
#pragma unroll 1
      for (int r = 0; r < MODREP; r++) st_relaxed(&g_mod[r * 2688 + col0 + c], (pack2(v, 0.f) & 0xFFFFu) | tg);
    }
    return;
  }
  if ((sb & 0xFFFFFFu) != SMEM0) bud = 0;
  uint32_t ep = 0;
  if (warp <= 8) {
    if (lane == 0) {
      const uint32_t cnt = bar_count(12 * warp);
#pragma unroll
      for (int i = 0; i < 12; i++) mbar_init(BAR(12 * warp + i), cnt);
      asm volatile("fence.mbarrier_init.release.cluster;" ::: "memory");
    }
    __syncwarp();
    if (warp == 1) {
#pragma unroll
      for (int i = 0; i < 6; i++) e_expect(BAR(B_XB5 + i), i < 2 ? 14336 : i < 4 ? 7168 : 4096);
    }
    if (warp == 8) {
      asm volatile(ELECT("mbarrier.expect_tx.relaxed.cta.shared::cta.b64 [%0], %1;") ::"r"(BAR(B_KALL)), "r"(min(rb1, 2) * 16384) : "memory");
      asm volatile(ELECT("mbarrier.expect_tx.relaxed.cta.shared::cta.b64 [%0], %1;") ::"r"(BAR(B_VALL)), "r"(min(rb1, 2) * 16384) : "memory");
    }
    bar_arrive(10, 384);
    bar_sync(6, 288);
  }
  auto cluster_wait = [&]() { asm volatile("barrier.cluster.wait.acquire.aligned;" ::: "memory"); };
  auto cluster_arrive = [&]() { asm volatile("barrier.cluster.arrive.relaxed.aligned;" ::: "memory"); };

  if (warp >= 8) {
    asm volatile("setmaxnreg.dec.sync.aligned.u32 56;");
    auto rows_mc = [&](const __nv_bfloat16* src, int page, int bar, int par) {
#pragma unroll 1
      for (int c = par; c < 7; c += 2) e_bulk_ld_mc(PAGE(page + c), src + c * 4096, 8192, BAR(bar + c));
    };
    const int a = warp - 10, hh = 2 * rb + a;
    if (warp > 8) {
      const int t96 = tid - 288;
      {
        uint16_t cc[5];
#pragma unroll
        for (int q = 0; q < 5; q++) cc[q] = t96 + 96 * q < 448 ? __ldg((const uint16_t*)P.pc + t96 + 96 * q) : (uint16_t)0;
        const uint32_t e0 = ld_relaxed(&g_epoch);
        if (warp == 9 && lane < 10) prefetch_map(&P.wmod + lane);
        cluster_arrive();
        bar_sync(10, 384);
        mbar_wait(BAR(B_MW));
        float acc[8] = {0, 0, 0, 0, 0, 0, 0, 0};
#pragma unroll
        for (int q = 0; q < 5; q++) fma8(acc, lds128(sb + OFF_MW + min(t96 + 96 * q, 447) * 16), silu_bf(bf_lo(cc[q])));
        ep = __shfl_sync(~0u, e0, 0) + 1;
        const float r = warp_red8(acc, lane);
        if (!(lane & 3)) sts32f(sb + OFF_RED + (warp - 9) * 32 + lane, r);
        bar_sync(9, 96);
        if (b < 112) {
          const uint32_t red = sb + OFF_RED + (t96 & 7) * 4;
          const uint32_t v = (pack2(lds32f(red) + lds32f(red + 32) + lds32f(red + 64), 0.f) & 0xFFFFu) | (ep << 16);
#pragma unroll 1
          for (int r = t96 >> 3; r < MODREP; r += 12) st_relaxed(&g_mod[r * 2688 + 8 * b + (t96 & 7)], v);
        }
      }
#pragma unroll 1
      for (int st = 0; st < 3; st++) {
        if (st != 1) {
          if (st && warp == 9) break;
          mbar_wait(BAR(st ? B_WO : B_X + 6));
          bool first = !st;
          const uint32_t* gm = g_mod + rb * 2688;
          const int nt = st ? 64 : 96, ni = st ? 265 : 223;
#pragma unroll 1
          for (int i0 = st ? t96 - 32 : t96; i0 <= ni; i0 += 192) {
            uint4 x[3];
            uint32_t bad;
            do {
              bad = 0;
#pragma unroll
              for (int q = 0; q < 3; q++) {
                const int i = min(i0 + nt * q, ni) - 224;
                x[q] = ld_relaxed4(&gm[i < 0 ? 672 * st + 896 + i * 4 : i < 28 ? 896 + 112 * c4 + i * 4 : 2240 - 112 + 56 * c8 + i * 4]);
              }
              if (first) { bar_arrive(11, 128); first = false; }
#pragma unroll
              for (int q = 0; q < 3; q++) bad |= mod_bad(x[q], ep << 16);
            } while (__any_sync(~0u, (bad >> 16) != 0) && --bud > 0);
#pragma unroll 1
            for (int q = 0; q < 3; q++) {
              const int i = min(i0 + nt * q, ni) - 224;
              if (i < 0) put_mod4(sb + (st ? OFF_MOD2 : OFF_MOD1), i + 224, x[0], st ? 0x3F003F00u : 0x3F803F80u);
              else { sts32(sb + OFF_GA + i * 8, __byte_perm(x[0].x, x[0].y, 0x5410)); sts32(sb + OFF_GA + i * 8 + 4, __byte_perm(x[0].z, x[0].w, 0x5410)); }
              x[0] = x[1]; x[1] = x[2];
            }
            if (!st) break;
          }
          __syncwarp();
          if (st) { e_arrive(BAR(B_MOD2)); break; }
          __syncwarp();
          bar_arrive(1, 384);
          if (warp > 9) l2_prefetch(a ? (const uint8_t*)P.pwin + b * 12544 : (const uint8_t*)P.pwo + b * 3136, a ? 12544 : 3136, lane);
        }
        const int kv = st;
        if (warp > 9) {
          mbar_wait(BAR(B_KRDY + 2 * kv + a));
          e_bulk_st(g_kv + (size_t)(b1 * 2 + kv) * 16384 + a * 8192, PAGE(12 + 6 * kv + a), 8192);
          e_publish(C_K + 128 * kv + b1);
          continue;
        }
        const uint32_t dst = PAGE(8 + 6 * kv), bar = BAR(B_KALL + kv);
        mbar_wait(BAR(B_XFREE + kv));
        uint32_t todo = rb1 >= 2 ? 3 : rb1;
        while (todo) {
          const uint32_t m = (__ballot_sync(~0u, reached(C_K + 128 * kv + max(b1 - 8 - 8 * (lane & 1), 0), 2 * ep)) | (--bud <= 0 ? 3u : 0u)) & todo;
          if (!m) continue;
          fence_async_glob();
          const int d = (m & 1) ^ 1;
          e_bulk_ld(dst + (1 - d) * 16384, g_kv + (size_t)((b1 - 8 - 8 * d) * 2 + kv) * 16384, 16384, bar);
          todo &= ~(1u << d);
        }
      }
    }
    if (warp == 8) {
      e_expect(BAR(B_MW), 7168);
      e_tma2d(sb + OFF_MW, &P.wmod, 8 * min(b, 111), 0, BAR(B_MW));
      e_tma2d(sb + OFF_MW + 3584, &P.wmod, 8 * min(b, 111), 224, BAR(B_MW));
#pragma unroll
      for (int c = 0; c < 7; c++) { e_expect(BAR(B_X + c), 16384); e_tma2d(PAGE(2 * c), &P.x, 64 * c, 128 * rb1, BAR(B_X + c)); }
      cluster_arrive();
      cluster_wait();
#pragma unroll 1
      for (int p = 0; p < 3; p++) {
        const int col = (56 * j1 & ~15) + (p == 2 ? 0 : 448 + 448 * p);
        e_expect(BAR(B_WK + p), 7 * 8192);
        if (p == 0) bar_sync(11, 128);
        if (p == 1) bar_sync(1, 384);
#pragma unroll 1
        for (int c = (p ^ kh) & 1; c < 7; c += 2) {
          if (c + 7 * p >= 13 && c + 7 * p < 16) { mbar_wait(BAR(B_XFREE)); mbar_wait(BAR(B_XFREE2)); }
          e_tma2d_mc(c + 7 * p == 13 ? PAGE(7) : PAGE((p == 0 ? 14 : p == 1 ? 21 : 0) + c), &P.wqkv, col, 64 * c, BAR(B_WK + p));
        }
      }
#pragma unroll 1
      for (int i = 0; i < 28; i++) {
        if (i == 7) {
          asm volatile(ELECT("cp.async.bulk.prefetch.L2.global [%0], 32768;") ::"l"((const uint8_t*)P.pwsp + (size_t)b * 65536) : "memory");
          asm volatile(ELECT("cp.async.bulk.prefetch.L2.global [%0], 32768;") ::"l"((const uint8_t*)P.pwsp + (size_t)b * 65536 + 32768) : "memory");
        }
        const uint32_t e = c_wprog[i], type = (e >> 25) & 3;
        if (e & 255) mbar_wait(BAR(e & 127), (e >> 7) & 1);
        const uint32_t bar = BAR((e >> 18) & 15);
        const int col = 112 * (type == 1 ? c4 : type == 2 ? c8 : cb4) + 448 * ((e >> 27) & 3);
        const int row = 64 * ((e >> 22) & 7) + (type == 3 ? 448 * kh : 0);
        const CUtensorMap* m = &P.wqkv + (2 * type - 1);
        if (e >> 29) e_expect(bar, (e >> 29) * 14336);
        e_tma2d(PAGE((e >> 8) & 31), m, col, row, bar);
        e_tma2d(PAGE((e >> 13) & 31), m + 1, col + (type == 1 ? 56 : 64), row, bar);
      }
    } else if (warp == 9) {
#pragma unroll
      for (int c = 0; c < 7; c++) e_expect(BAR(B_A3 + c), 8192);
      mbar_wait(BAR(B_ATT)); mbar_wait(BAR(B_ATT2));
      poll(C_O + h3, 8 * ep);
      rows_mc(g_o + h3 * 28672, 8, B_A3, kh);
      l2_prefetch((const uint8_t*)P.pwout + b * 6272, 6272, lane);
      mbar_wait(BAR(B_Z2PASS));
#pragma unroll 1
      for (int i = 0; i < 16; i++) {
        const int s = i & 3, h = 16 * kh + (i < 8 ? 2 * i : 2 * i - 15);
        if (i == 0 || i == 3) {
          poll(C_Z + 16 * kh + 2 * (lane & 7) + (i & 1), 8 * ep);
          e_bulk_ld(PAGE(26) + (i & 1) * 4096, g_st2 + (2 * kh + (i & 1)) * 512, 4096, BAR(B_RAW + (i & 1)));
        }
        if (i == 1) mbar_wait(BAR(B_STGDONE));
        if (i) mbar_wait(BAR(i >= 4 ? B_S5E + s : B_Z1C + i - 1), i >= 4 ? (i >> 2) - 1 & 1 : 0);
        const uint32_t dst = PAGE(s == 0 ? 20 : 6 * s - 4);
        const uint8_t* src = g_z2t + (size_t)h * FH * 128;
        e_expect(BAR(B_S5F + s), 46080);
        e_tma2d(dst, &P.wsp, 64 * h, 128 * rb, BAR(B_S5F + s));
        e_bulk_ld(dst + 16384, src + 14336 * c8, 14336, BAR(B_S5F + s));
        e_bulk_ld(dst + 30720, src + 14336 * (c8 ^ 1), 14336, BAR(B_S5F + s));
        e_bulk_ld(dst + 45056, g_s.zs + h * 1024, 1024, BAR(B_S5F + s));
      }
    } else {
#pragma unroll
      for (int c = 0; c < 7; c++) e_expect(BAR(B_A4 + 7 * a + c), c ? 8192 : 12288);
      mbar_wait(BAR(B_S3MMA)); mbar_wait(BAR(B_S3MMA2));
      poll(C_X + hh, 4 * ep);
      e_bulk_ld(sb + (a ? OFF_RAW1B : OFF_MW), g_st1 + hh * 512, 4096, BAR(B_A4 + 7 * a));
      rows_mc(g_x1 + hh * 28672, 7 * a, B_A4 + 7 * a, kh ^ a);
      mbar_wait(BAR(B_STG + a));
      e_release(C_Z + hh);
      e_arrive(BAR(B_STGDONE));
      mbar_wait(BAR(B_RAW + a));
#pragma unroll 1
      for (int q = 8 * a; q < 8 * a + 8; q++) {
        const uint4 v = lds128(PAGE(26) + q * 512 + lane * 16);
        const float m0 = __uint_as_float(v.x) * (1.f / 896.f), m1 = __uint_as_float(v.z) * (1.f / 896.f);
        const float r0 = rsqrtf(fmaxf(fmaf(__uint_as_float(v.y), 1.f / 896.f, -m0 * m0), 0.f) + 1e-5f);
        const float r1 = rsqrtf(fmaxf(fmaf(__uint_as_float(v.w), 1.f / 896.f, -m1 * m1), 0.f) + 1e-5f);
        sts32(sb + OFF_R5 + (q * 64 + perm64(2 * lane)) * 2, pack2(r0, r1));
      }
      e_arrive(BAR(B_ST2 + a));
      mbar_wait(BAR(B_QPASS), 1);
      poll(C_U + 2 * rb + kh, 4 * ep);
#pragma unroll 1
      for (int c = 0; c < 7; c++) {
        if (c == 4 && a) mbar_wait(BAR(B_XRD));
        if (c == 5) mbar_wait(BAR(B_A6RD + a));
        e_expect(BAR(B_A4 + 7 * a + c), 8192);
        e_bulk_ld(PAGE(16 + 5 * a + (c < 5 ? c : c - 5)), g_u + (2 * hh + kh) * 28672 + c * 4096, 8192, BAR(B_A4 + 7 * a + c));
      }
    }
    __syncwarp();
    if (warp > 8) cluster_wait();
  } else {
    asm volatile("setmaxnreg.inc.sync.aligned.u32 224;");
    const int a = warp >> 2, w = warp & 3, j = lane & 3, g = lane >> 2;
    const int r0 = 16 * w + g;
    const uint32_t lx = lane & 7, lhi = lane >> 4;
    uint32_t lda[4];
#pragma unroll
    for (int ks = 0; ks < 4; ks++) lda[ks] = sb + (16 * w + (lane & 15)) * 128 + (((2 * ks + lhi) ^ lx) << 4);

    cluster_arrive();
    const uint32_t ldc = sb + lhi * 1024 + (16 * w + (lane & 15)) * 16;
    const int cmo = r0 * 8 + 2 * j;
    if (a == 1) bar_arrive(4, 256);

    uint32_t qf[14];
    {
      uint32_t A[28][4];
      {
        float s2[2][4] = {}, q2[2][4] = {};
        uint32_t pv0 = 0, pv1 = 0;
#pragma unroll
        for (int c = 0; c < 7; c++) {
          mbar_wait(BAR(B_X + c));
#pragma unroll
          for (int ks = 0; ks < 4; ks++) ldsm4(A[4 * c + ks], lda[ks] + a * PG + 2 * c * PG);
#pragma unroll
          for (int ks = 0; ks < 4; ks++) rowsum_mma(s2[ks & 1], A[4 * c + ks]);
          if (c == 0) {
            const float m0 = (s2[0][0] + s2[1][0]) * (1.f / 64.f), m1 = (s2[0][2] + s2[1][2]) * (1.f / 64.f);
            pv0 = pack2(m0, m0); pv1 = pack2(m1, m1);
          }
          if (c == 6) { e_arrive(BAR(B_XFREE)); cluster_wait(); e_arrive_remote(mapa(BAR(B_XFREE2), peer)); }
#pragma unroll
          for (int ks = 0; ks < 4; ks++) {
            uint32_t* x = A[4 * c + ks];
            x[0] = hsub2(x[0], pv0); x[1] = hsub2(x[1], pv1); x[2] = hsub2(x[2], pv0); x[3] = hsub2(x[3], pv1);
            uint32_t sq[4] = {hmul2(x[0], x[0]), hmul2(x[1], x[1]), hmul2(x[2], x[2]), hmul2(x[3], x[3])};
            rowsum_mma(q2[ks & 1], sq);
          }
        }
        const float m0 = fmaf(s2[0][0] + s2[1][0], 1.f / 448.f, -bf_lo(pv0)), m1 = fmaf(s2[0][2] + s2[1][2], 1.f / 448.f, -bf_lo(pv1));
        const float rs0 = rsqrtf(fmaxf(fmaf(q2[0][0] + q2[1][0], 1.f / 448.f, -m0 * m0), 0.f) + 1e-5f);
        const float rs1 = rsqrtf(fmaxf(fmaf(q2[0][2] + q2[1][2], 1.f / 448.f, -m1 * m1), 0.f) + 1e-5f);
        const uint32_t rp0 = pack2(rs0, rs0), rp1 = pack2(rs1, rs1), nm0 = pack2(-m0 * rs0, -m0 * rs0), nm1 = pack2(-m1 * rs1, -m1 * rs1);
#pragma unroll
        for (int i = 0; i < 28; i++) {
          A[i][0] = hfma2(A[i][0], rp0, nm0); A[i][1] = hfma2(A[i][1], rp1, nm1); A[i][2] = hfma2(A[i][2], rp0, nm0); A[i][3] = hfma2(A[i][3], rp1, nm1);
        }
      }
      bar_sync(1, 384);
      if (a == 1) bar_sync(7, 256);
#pragma unroll
      for (int h = 0; h < 14; h++) {
        uint4 cv = lds128(sb + OFF_MOD1 + j * 16 + h * 64), sv = lds128(sb + OFF_MOD1 + 896 + j * 16 + h * 64);
        uint32_t* p = A[2 * h]; uint32_t* q = A[2 * h + 1];
        p[0] = hfma2(p[0], cv.x, sv.x); p[1] = hfma2(p[1], cv.x, sv.x); p[2] = hfma2(p[2], cv.y, sv.y); p[3] = hfma2(p[3], cv.y, sv.y);
        q[0] = hfma2(q[0], cv.z, sv.z); q[1] = hfma2(q[1], cv.z, sv.z); q[2] = hfma2(q[2], cv.w, sv.w); q[3] = hfma2(q[3], cv.w, sv.w);
      }
      if (a == 0) asm volatile("bar.arrive 7, 256;" ::"r"(A[27][3]), "r"(A[20][0]), "r"(A[13][1]) : "memory");
      const uint32_t st_addr = sb + (12 + a) * PG + (16 * w + ((lane >> 3) & 1) * 8 + lx) * 128;
#pragma unroll 1
      for (int p = 0; p < 3; p++) {
        float acc[28];
        const uint32_t wb = (p == 0 ? 14 : p == 1 ? 21 : 0) * (PG / 16) + (j1 & 1), wb6 = p == 1 ? PG / 16 + (j1 & 1) : wb;
        mbar_wait(BAR(B_WK + p));
        bar_sync(4 + a, 256);
        wg_fence();
#pragma unroll
        for (int i = 0; i < 28; i++) wg_rs56<1>(acc, A[i], desc(i < 24 ? wb : wb6, i * 2048, 0), i != 0);
        wg_commit();
        if (p < 2 || a == 0) bar_arrive(5 - a, 256);
        wg_wait<0>(); keep<28>(acc);
        e_arrive(BAR(B_KPASS + p));
#pragma unroll
        for (int i = 0; i < 14; i++) qf[i] = pack2(acc[2 * i], acc[2 * i + 1]);
        if (p < 2) {
          if (p == 1 || rb1 < 2) mbar_wait(BAR(B_XFREE + p));
          if (rb1 < 2) {
#pragma unroll 1
            for (int i = tid; i < (2 - rb1) * 1024; i += 256) sts128(PAGE(8 + 6 * p) + i * 16, make_uint4(0, 0, 0, 0));
          }
          const uint32_t fill = (p == 1 && !(j & 1)) ? 0x3F80u : 0u;
          const uint32_t ta = st_addr + p * 6 * PG;
          stsm4(ta + ((lhi ^ lx) << 4), qf[0], qf[1], qf[2], qf[3]);
          stsm4(ta + (((2 + lhi) ^ lx) << 4), qf[4], qf[5], j < 2 ? qf[6] : fill, j < 2 ? qf[7] : fill);
          stsm4(ta + (((4 + lhi) ^ lx) << 4), j < 2 ? fill : qf[6], j < 2 ? fill : qf[7], qf[8], qf[9]);
          stsm4(ta + (((6 + lhi) ^ lx) << 4), qf[10], qf[11], qf[12], qf[13]);
          fence_async_smem();
          e_arrive(BAR(B_KRDY + 2 * p + a)); e_arrive(BAR(B_KALL + p));
        }
      }
    }
    {
      const int q0 = 128 * rb1 + 64 * a;
      const float sc = 0.18898223650461362f * 1.4426950408889634f;
      const float ninf = __int_as_float(0xff800000);
      uint32_t ow[14];
      const int dd = r0 - 2 * j;
      mbar_wait(BAR(B_KALL));
#pragma unroll 1
      for (int hd = 0; hd < 2; hd++) {
        const uint32_t kb = a * (PG / 16) + hd * 4;
        float sm[96], s0[32], s4[32];
        wg_fence();
#pragma unroll
        for (int ks = 0; ks < 2; ks++) {
          wg_rs64<0>(s0, qf + 4 * ks, desc(kb, 8 * PG + ks * 32, 16), ks);
          wg_rs64<0>(s4, qf + 4 * ks, desc(kb, 12 * PG + ks * 32, 16), ks);
          wg_rs192<0>(sm, qf + 4 * ks, desc(kb, 9 * PG + ks * 32, 16), ks);
        }
        wg_commit();
        wg_wait<0>(); keep<96>(sm); keep<32>(s0); keep<32>(s4);
#pragma unroll
        for (int i = 0; i < 8; i++) qf[i] = qf[i + 6];
        if (q0 < 256) {
#pragma unroll
          for (int i = 0; i < 32; i++) s0[i] = ninf;
        }
#pragma unroll
        for (int i = 0; i < 32; i++) { int t = i >> 2, e = (i >> 1) & 1, f = i & 1; s4[i] = (8 * t + f - 8 * e <= dd) ? s4[i] : s0[i]; }
        float mx[2] = {s4[0], s4[2]};
#pragma unroll
        for (int i = 0; i < 32; i++) mx[(i >> 1) & 1] = fmaxf(mx[(i >> 1) & 1], s4[i]);
#pragma unroll
        for (int k = 0; k < 3; k++) {
          float t[2] = {sm[32 * k], sm[32 * k + 2]};
#pragma unroll
          for (int i = 0; i < 32; i++) t[(i >> 1) & 1] = fmaxf(t[(i >> 1) & 1], sm[32 * k + i]);
          if (q0 - 192 + 64 * k >= 0) { mx[0] = fmaxf(mx[0], t[0]); mx[1] = fmaxf(mx[1], t[1]); }
        }
        mx[0] = -quad_max(mx[0]) * sc; mx[1] = -quad_max(mx[1]) * sc;
        if (hd | a) mbar_wait(BAR(B_TURN - 1 + 2 * hd + a));
        asm volatile("" : "+f"(mx[0]), "+f"(mx[1]) :: "memory");
        uint32_t pm[48], p0[16], p4[16];
#pragma unroll
        for (int k = 0; k < 3; k++) {
          const bool ok = q0 - 192 + 64 * k >= 0;
          const float m0 = ok ? mx[0] : ninf, m1 = ok ? mx[1] : ninf;
#pragma unroll
          for (int i = 16 * k; i < 16 * k + 16; i++) {
            const float m = (i & 1) ? m1 : m0;
            pm[i] = pack2(ex2v(fmaf(sm[2 * i], sc, m)), ex2v(fmaf(sm[2 * i + 1], sc, m)));
          }
        }
#pragma unroll
        for (int i = 0; i < 16; i++) {
          const uint32_t pw = pack2(ex2v(fmaf(s4[2 * i], sc, mx[i & 1])), ex2v(fmaf(s4[2 * i + 1], sc, mx[i & 1])));
          const int lim = 8 * (i >> 1) - 8 * (i & 1);
          const uint32_t mk = (lim + 1 <= dd) ? 0xFFFFFFFFu : (lim <= dd ? 0x0000FFFFu : 0u);
          p4[i] = pw & mk; p0[i] = pw & ~mk;
        }
        if (hd == 0 || a == 0) {
          const uint32_t dep = (pm[3] | pm[9] | pm[15]) | (pm[21] | pm[27] | pm[33]) | (pm[39] | pm[45] | p4[2]) | (p0[7] | p4[12] | p0[15]);
          __syncwarp();
          if (lane == 0) mbar_arrive(BAR(B_TURN + 2 * hd + a) + ((dep >> 31) << 3));
        }
        if (hd == 0) mbar_wait(BAR(B_VALL));
        float o[16];
        wg_fence();
#pragma unroll
        for (int s = 0; s < 12; s++) wg_rs32<1>(o, pm + 4 * s, desc(kb, 15 * PG + s * 2048, 0), s);
#pragma unroll
        for (int s = 0; s < 4; s++) wg_rs32<1>(o, p0 + 4 * s, desc(kb, 14 * PG + s * 2048, 0), 1);
#pragma unroll
        for (int s = 0; s < 4; s++) wg_rs32<1>(o, p4 + 4 * s, desc(kb, 18 * PG + s * 2048, 0), 1);
        wg_commit();
        wg_wait<0>(); keep<16>(o);
        const int src = (lane & 28) | (hd ? 0 : 2);
        const float l0 = rcp(__shfl_sync(~0u, hd ? o[0] : o[12], src)), l1 = rcp(__shfl_sync(~0u, hd ? o[2] : o[14], src));
        const bool keep3 = hd == 1 && j < 2;
        const uint32_t e0 = ow[12], e1 = ow[13];
#pragma unroll
        for (int i = 0; i < 6; i++) ow[i] = ow[i + 6];
#pragma unroll
        for (int t = 0; t < 4; t++) { ow[6 + 2 * t] = pack2(o[4 * t] * l0, o[4 * t + 1] * l0); ow[7 + 2 * t] = pack2(o[4 * t + 2] * l1, o[4 * t + 3] * l1); }
        ow[6] = keep3 ? e0 : ow[6]; ow[7] = keep3 ? e1 : ow[7];
      }
      store_cm<7>(ow, g_o + ((2 * rb1 + a) * 56 + 7 * j1) * 512 + cmo);
      if (w == 0 && lane < 4) stg128(g_st2 + st2pos(2 * rb1 + a) + 8 * j1 + 2 * lane, make_uint4(0, 0, 0, 0));
      e_arrive(BAR(B_ATT)); e_arrive_remote(mapa(BAR(B_ATT2), peer));
      bar_sync(2 + a, 128);
      if (w == 0) e_release(C_O + 2 * rb1 + a);
    }
    {
      uint32_t xr[16];
      {
        const int rr = (lane * 37) >> 8, cc = lane - 7 * rr;
        const uint32_t stg = PAGE(26) + warp * 1024;
        uint4 v[4];
        if (lane < 28) {
#pragma unroll
          for (int k = 0; k < 4; k++) v[k] = __ldg((const uint4*)(P.px + (size_t)(64 * h3 + 16 * w + 4 * k + rr) * DM + 112 * c4 + 56 * a) + cc);
        }
#pragma unroll
        for (int hf = 0; hf < 2; hf++) {
          if (lane < 28) { sts128(stg + lane * 16, v[2 * hf]); sts128(stg + 448 + lane * 16, v[2 * hf + 1]); }
          __syncwarp();
          uint32_t m[8];
          ldsm4(m, stg + lx * 112 + (lane >> 3) * 16);
          ldsm4(m + 4, stg + lx * 112 + min(4 + (lane >> 3), 6) * 16);
#pragma unroll
          for (int t = 0; t < 7; t++) xr[2 * t + hf] = m[t];
          __syncwarp();
        }
      }
      e_arrive(BAR(B_XST));
      float acc[28];
      mbar_wait(BAR(B_WO));
#pragma unroll 1
      for (int c = 0; c < 7; c++) {
        mbar_wait(BAR(B_A3 + c), 1);
        wg_fence();
#pragma unroll
        for (int ks = 0; ks < 4; ks++) wg_ss56<1>(acc, (uint64_t)(c * (PG / 16) + ((SMEM0 + 8 * PG + ks * 2048) >> 4) + (64u << 16)) | (uint64_t)8 << 32, desc(((c < 4 ? 2 * c : 2 * c + 12) + a) * (PG / 16), ks * 2048, 0), (c | ks) != 0);
      }
      wg_commit();
      mbar_wait(BAR(B_MOD2));
      wg_wait<0>(); keep<28>(acc);
      e_arrive(BAR(B_S3MMA)); e_arrive_remote(mapa(BAR(B_S3MMA2), peer));
#pragma unroll
      for (int t = 0; t < 7; t++) {
        const uint32_t ga = lds32(sb + OFF_GA + a * 112 + j * 4 + t * 16);
        xr[2 * t] = hfma2(ga, pack2(acc[4 * t], acc[4 * t + 1]), xr[2 * t]);
        xr[2 * t + 1] = hfma2(ga, pack2(acc[4 * t + 2], acc[4 * t + 3]), xr[2 * t + 1]);
      }
      store_cm<7>(xr, g_x1 + (h3 * 56 + 14 * c4 + 7 * a) * 512 + cmo);
      const uint32_t p0 = __byte_perm(__shfl_sync(~0u, xr[0], lane & 28), 0, 0x1010), p1 = __byte_perm(__shfl_sync(~0u, xr[1], lane & 28), 0, 0x1010);
      xr[14] = p0; xr[15] = p1;
      float s[4] = {}, q[4] = {};
#pragma unroll
      for (int i = 0; i < 4; i++) {
        uint32_t d[4], e[4];
#pragma unroll
        for (int k = 0; k < 4; k++) { d[k] = hsub2(xr[4 * i + k], (k & 1) ? p1 : p0); e[k] = hmul2(d[k], d[k]); }
        rowsum_mma(s, d);
        rowsum_mma(q, e);
      }
      if (j < 2) {
        const float sd = j ? s[2] : s[0];
        g_st1[(h3 * 8 + 2 * c4 + a) * 64 + r0 + 8 * j] = make_float2(fmaf(bf_lo(j ? p1 : p0), 56.f, sd), fmaf(-sd * (1.f / 56.f), sd, j ? q[2] : q[0]));
      }
      bar_sync(1, 256);
      if (warp == 0) e_release(C_X + h3);
    }
    uint32_t zp[28];
    {
      uint32_t A[28][4];
      mbar_wait(BAR(B_MOD2));
      uint32_t rh[2], rl[2], mr[2];
      mbar_wait(BAR(B_A4 + 7 * a));
#pragma unroll
      for (int e = 0; e < 2; e++) {
        float2 q[8];
        float mean = 0.f, m2 = 0.f;
#pragma unroll
        for (int i = 0; i < 8; i++) { q[i] = lds64f(sb + (a ? OFF_RAW1B : OFF_MW) + (r0 + 8 * e) * 8 + i * 512); mean += q[i].x; m2 += q[i].y; }
        mean *= 1.f / 448.f;
#pragma unroll
        for (int i = 0; i < 8; i++) { const float d = fmaf(q[i].x, 1.f / 56.f, -mean); m2 = fmaf(56.f * d, d, m2); }
        const float rstd = rsqrtf(fmaxf(m2, 0.f) * (1.f / 448.f) + 1e-5f);
        rh[e] = pack2(rstd, rstd);
        const float lo = rstd - bf_lo(rh[e]), nm = -mean * rstd;
        rl[e] = pack2(lo, lo); mr[e] = pack2(nm, nm);
      }
      if (a == 1) bar_arrive(4, 256);
#pragma unroll
      for (int c = 0; c < 7; c++) {
        if (c) mbar_wait(BAR(B_A4 + 7 * a + c));
#pragma unroll
        for (int ks = 0; ks < 4; ks++) ldsm4(A[4 * c + ks], ldc + 7 * a * PG + c * PG + ks * 2048);
        if (c == 6) e_arrive(BAR(B_A4RD + a));
        if (c == 1 && a == 0) e_arrive(BAR(B_A4E));
#pragma unroll
        for (int h = 0; h < 2; h++) {
          uint4 cv = lds128(sb + OFF_MOD2 + j * 16 + (2 * c + h) * 64), sv = lds128(sb + OFF_MOD2 + 896 + j * 16 + (2 * c + h) * 64);
          uint32_t cw[4] = {cv.x, cv.y, cv.z, cv.w}, sw[4] = {sv.x, sv.y, sv.z, sv.w};
#pragma unroll
          for (int i = 0; i < 8; i++) {
            uint32_t& x = A[4 * c + 2 * h + (i >> 2)][i & 3];
            x = hfma2(hfma2(x, rh[i & 1], hfma2(x, rl[i & 1], mr[i & 1])), cw[i >> 1], sw[i >> 1]);
          }
        }
      }
#pragma unroll 1
      for (int p = 0; p < 2; p++) {
        float acc[56];
        mbar_wait(BAR(B_Z2W + 3 * p));
        bar_sync(4 + a, 256);
#pragma unroll
        for (int c = 0; c < 7; c++) {
          if (c == 2 || c == 4) { if (p) mbar_wait(BAR(B_Z1W + c / 2)); }
          if (c == 3 || c == 6) { if (!p) mbar_wait(BAR(B_Z2W + c / 3)); }
          wg_fence();
          const int q2 = c < 2 ? 16 + 2 * c : c == 2 ? 15 : c < 6 ? 14 + 2 * c : 0, l2 = c == 2 ? 11 : 1;
          const int q1 = c == 0 ? 4 : c == 1 ? 6 : c == 2 ? 9 : c == 3 ? 11 : c == 4 ? 16 : c == 5 ? 18 : 0, l1 = c == 1 ? 8 : 1;
          const uint32_t d16 = p ? (q1 * (PG / 16)) | (l1 * (PG / 16)) << 16 : (q2 * (PG / 16)) | (l2 * (PG / 16)) << 16;
#pragma unroll
          for (int ks = 0; ks < 4; ks++) wg_rs112<1>(acc, A[4 * c + ks], desc(d16, ks * 2048, 0), (c | ks) != 0);
          wg_commit();
          if (c == 3) { wg_wait<2>(); e_arrive(BAR(B_Z2C + p)); }
          if (c == 5) { wg_wait<2>(); if (p) e_arrive(BAR(B_Z1C + 1)); }
        }
        if (p == 0 || a == 0) bar_arrive(5 - a, 256);
        wg_wait<1>();
        if (p) e_arrive(BAR(B_Z1C + 2));
        wg_wait<0>(); keep<56>(acc);
        if (!p) e_arrive(BAR(B_Z2PASS));
        float s2[2] = {0.f, 0.f}, q2[2] = {0.f, 0.f};
#pragma unroll
        for (int i = 0; i < 28; i++) {
          const float x = gelu_h(acc[2 * i]), y = gelu_h(acc[2 * i + 1]);
          zp[i] = pack2(x, y);
          s2[i & 1] += x + y;
          q2[i & 1] = fmaf(x, x, fmaf(y, y, q2[i & 1]));
        }
        if (p == 0) {
          const uint32_t sp = PAGE(a ? 7 : 2), stg = sp + (lhi * 8 + lx) * 128 + (((2 * w + ((lane >> 3) & 1)) ^ lx) << 4);
#pragma unroll
          for (int t = 0; t < 7; t++) stsm4t(stg + t * 2048, zp[4 * t], zp[4 * t + 1], zp[4 * t + 2], zp[4 * t + 3]);
          float sv = (j & 1) ? s2[1] : s2[0], qv = (j & 1) ? q2[1] : q2[0];
          sv += __shfl_xor_sync(~0u, (j & 1) ? s2[0] : s2[1], 1); qv += __shfl_xor_sync(~0u, (j & 1) ? q2[0] : q2[1], 1);
          sv += __shfl_xor_sync(~0u, sv, 2); qv += __shfl_xor_sync(~0u, qv, 2);
          if (j < 2) {
            asm volatile("red.relaxed.gpu.global.add.v2.f32 [%0], {%1, %2};" ::"l"(g_st2 + st2pos(2 * rb + a) + r0 + 8 * j), "f"(sv), "f"(qv) : "memory");
            *(uint16_t*)(g_s.zs + (2 * rb + a) * 1024 + c8 * 128 + (((2 * w + j) ^ c8) << 4) + g * 2) = (uint16_t)pack2(sv * (1.f / 896.f), 0.f);
          }
          bar_sync(2 + a, 128);
          uint8_t* zg = g_z2t + ((size_t)(2 * rb + a) * FH + 112 * c8) * 128 + (tid & 127) * 16;
#pragma unroll
          for (int t = 0; t < 7; t++) stg128(zg + t * 2048, lds128(sp + (tid & 127) * 16 + t * 2048));
          e_arrive(BAR(B_STG + a));
        }
      }
    }
    {
      float acc[116];
      uint32_t A[2][16];
      const size_t row = 128 * rb + 64 * a + r0;
      uint16_t bs0, bs1;
      asm volatile("ld.global.nc.u16 %0, [%2];\nld.global.nc.u16 %1, [%2+16];" : "=h"(bs0), "=h"(bs1) : "l"(P.pbsp + row));
      auto prep = [&](int i, uint32_t* Af) {
        if ((i & 7) == 0) {
          mbar_wait(BAR(B_ST2 + (i >> 3)));
          if (i) {
            e_arrive_remote(mapa(BAR(B_X5FREE), peer));
          }
        }
        const int s = i & 3;
        mbar_wait(BAR(B_S5F + s), (i >> 2) & 1);
        const uint32_t pa = PG * (s == 0 ? 20 : 6 * s - 4) + a * PG;
#pragma unroll
        for (int ks = 0; ks < 4; ks++) ldsm4(Af + 4 * ks, lda[ks] + pa);
#pragma unroll
        for (int h = 0; h < 2; h++) {
          uint4 rv = lds128(sb + OFF_R5 + i * 128 + j * 32 + h * 16);
          uint32_t* p = Af + 8 * h;
          p[0] = hmul2(p[0], rv.x); p[1] = hmul2(p[1], rv.x); p[2] = hmul2(p[2], rv.y); p[3] = hmul2(p[3], rv.y);
          p[4] = hmul2(p[4], rv.z); p[5] = hmul2(p[5], rv.z); p[6] = hmul2(p[6], rv.w); p[7] = hmul2(p[7], rv.w);
        }
      };
      auto mma = [&](int i, const uint32_t* Af) {
        const int s = i & 3;
        wg_fence();
#pragma unroll
        for (int ks = 0; ks < 4; ks++) wg_rs232<0>(acc, Af + 4 * ks, desc((s == 0 ? 22 : 6 * s - 2) * (PG / 16), ks * 32, 16), (i | ks) != 0);
        wg_commit();
        wg_wait<1>();
        if (i > 0) e_arrive(BAR(i < 14 ? B_S5E + ((i - 1) & 3) : B_KPASS - 14 + i));
      };
#pragma unroll 1
      for (int i = 0; i < 16; i += 2) {
        if (i > 0) mma(i - 1, A[1]);
        prep(i, A[0]);
        mma(i, A[0]);
        prep(i + 1, A[1]);
      }
      mma(15, A[1]);
      mbar_wait(BAR(B_X5FREE));
      wg_wait<0>(); keep<116>(acc);
      float c0 = quad_sum(acc[112] + acc[113]), c1 = quad_sum(acc[114] + acc[115]);
      e_arrive(BAR(B_QPASS));
      const uint32_t xw = (a ? OFF_XB5_1 : OFF_XB5_0) + w * 3584, xoff = xw + lane * 16;
      const uint32_t rx = mapa(sb + xoff, peer), rbar = mapa(BAR(B_XB5 + a), peer);
#pragma unroll
      for (int q = 0; q < 7; q++) {
        const float* s = acc + 56 + 8 * q;
        st_async4(rx + q * 512, pack2(s[0] - c0, s[1] - c0), pack2(s[2] - c1, s[3] - c1), pack2(s[4] - c0, s[5] - c0), pack2(s[6] - c1, s[7] - c1), rbar);
      }
      c0 = bf_lo(bs0) - c0; c1 = bf_lo(bs1) - c1;
      uint32_t gk[28];
#pragma unroll
      for (int i = 0; i < 28; i++) { const float cc = (i & 1) ? c1 : c0; gk[i] = pack2(acc[2 * i] + cc, acc[2 * i + 1] + cc); }
      mbar_wait(BAR(B_XB5 + a));
#pragma unroll
      for (int q = 0; q < 7; q++) {
        const uint4 v = lds128(sb + xoff + q * 512);
        zp[4 * q] = hmul2(hadd2(gk[4 * q], v.x), zp[4 * q]); zp[4 * q + 1] = hmul2(hadd2(gk[4 * q + 1], v.y), zp[4 * q + 1]);
        zp[4 * q + 2] = hmul2(hadd2(gk[4 * q + 2], v.z), zp[4 * q + 2]); zp[4 * q + 3] = hmul2(hadd2(gk[4 * q + 3], v.w), zp[4 * q + 3]);
      }
      store_cm<14>(zp, g_u + ((2 * rb + a) * 112 + 14 * c8) * 512 + cmo);
      __syncwarp();
      e_arrive_remote(mapa(BAR(B_X6FREE), peer));
      if (a == 1) e_arrive(BAR(B_XRD));
      bar_sync(1, 256);
      if (warp == 0) e_release(C_U + rb * 2 + (c8 >> 2));
    }
    {
      uint32_t xr[14];
#pragma unroll
      for (int t = 0; t < 14; t++) xr[t] = __ldcg((const uint32_t*)(g_x1 + ((2 * rb + a) * 56 + 7 * c8 + (t >> 1)) * 512 + (t & 1) * 64 + cmo));
      float acc[56];
      uint32_t A[2][16];
      auto ld6 = [&](int c, uint32_t* Af) {
        mbar_wait(BAR(B_A4 + 7 * a + c), 1);
#pragma unroll
        for (int ks = 0; ks < 4; ks++) ldsm4(Af + 4 * ks, ldc + (16 + 5 * a + (c < 5 ? c : c - 5)) * PG + ks * 2048);
      };
      auto mma6 = [&](int c, const uint32_t* Af) {
        wg_fence();
#pragma unroll
        for (int ks = 0; ks < 4; ks++) wg_rs112<1>(acc, Af + 4 * ks, desc(c * (PG / 8), 2 * PG + ks * 2048, PG), (c | ks) != 0);
        wg_commit();
        wg_wait<1>();
      };
      mbar_wait(BAR(B_B6)); mbar_wait(BAR(B_B6 + 1)); mbar_wait(BAR(B_B6 + 2));
#pragma unroll 1
      for (int c = 0; c < 7; c += 2) {
        if (c) mma6(c - 1, A[1]);
        ld6(c, A[0]);
        mma6(c, A[0]);
        if (c < 6) ld6(c + 1, A[1]);
        if (c == 0) e_arrive(BAR(B_A6RD + a));
      }
      mbar_wait(BAR(B_X6FREE));
      wg_wait<0>(); keep<56>(acc);
      uint32_t ps[14], pk[14];
#pragma unroll
      for (int i = 0; i < 14; i++) {
        const uint32_t lo = pack2(acc[2 * i], acc[2 * i + 1]), hi = pack2(acc[28 + 2 * i], acc[29 + 2 * i]);
        ps[i] = kh ? lo : hi; pk[i] = kh ? hi : lo;
      }
      const uint32_t xw = a * PG + w * 2048, xoff = xw + lane * 16;
      const uint32_t rx = mapa(sb + xoff, peer), rbar = mapa(BAR(B_XB6 + a), peer);
#pragma unroll
      for (int q = 0; q < 3; q++) st_async4(rx + q * 512, ps[4 * q], ps[4 * q + 1], ps[4 * q + 2], ps[4 * q + 3], rbar);
      st_async2(rx + 1536 - lane * 8, ps[12], ps[13], rbar);
      mbar_wait(BAR(B_XB6 + a));
#pragma unroll
      for (int q = 0; q < 3; q++) { uint4 v = lds128(sb + xoff + q * 512); ps[4 * q] = v.x; ps[4 * q + 1] = v.y; ps[4 * q + 2] = v.z; ps[4 * q + 3] = v.w; }
      { float2 v = lds64f(sb + xw + 1536 + lane * 8); ps[12] = __float_as_uint(v.x); ps[13] = __float_as_uint(v.y); }
#pragma unroll
      for (int t = 0; t < 7; t++) {
        const uint32_t gb = lds32(sb + OFF_GB + j * 4 + t * 16);
        xr[2 * t] = hfma2(gb, hadd2(pk[2 * t], ps[2 * t]), xr[2 * t]);
        xr[2 * t + 1] = hfma2(gb, hadd2(pk[2 * t + 1], ps[2 * t + 1]), xr[2 * t + 1]);
      }
      __syncwarp();
      store_rows<7>(xr, sb + xw, P.out + (size_t)(128 * rb + 64 * a + 16 * w) * DM + 56 * c8, DM, lane);
    }
    if (b == 0 && tid == 0) st_relaxed(&g_epoch, ld_relaxed(&g_epoch) + 1);
  }
}

typedef CUresult (*EncodeFn)(CUtensorMap*, CUtensorMapDataType, cuuint32_t, void*, const cuuint64_t*, const cuuint64_t*, const cuuint32_t*,
                             const cuuint32_t*, CUtensorMapInterleave, CUtensorMapSwizzle, CUtensorMapL2promotion, CUtensorMapFloatOOBfill);

void make_map(EncodeFn enc, CUtensorMap* m, const void* ptr, uint64_t inner, uint64_t outer, uint32_t bi, uint32_t bo,
              CUtensorMapSwizzle sw = CU_TENSOR_MAP_SWIZZLE_128B) {
  cuuint64_t dims[2] = {inner, outer}, strides[1] = {inner * 2};
  cuuint32_t box[2] = {bi, bo}, es[2] = {1, 1};
  enc(m, CU_TENSOR_MAP_DATA_TYPE_BFLOAT16, 2, const_cast<void*>(ptr), dims, strides, box, es, CU_TENSOR_MAP_INTERLEAVE_NONE,
      sw, CU_TENSOR_MAP_L2_PROMOTION_L2_256B, CU_TENSOR_MAP_FLOAT_OOB_FILL_NONE);
}

}

extern "C" void kernel_launch(void* const* d_in, const int* in_sizes, int n_in, void* d_out, int out_size) {
  static EncodeFn enc = nullptr;
  if (!enc) {
    void* fn = nullptr;
    cudaDriverEntryPointQueryResult st;
    cudaGetDriverEntryPoint("cuTensorMapEncodeTiled", &fn, cudaEnableDefault, &st);
    enc = (EncodeFn)fn;
    cudaFuncSetAttribute(fused_kernel, cudaFuncAttributeMaxDynamicSharedMemorySize, SMEM_BYTES);
  }
  typedef const __nv_bfloat16* bp;
  Params P;
  P.px = (bp)d_in[0]; P.pwqkv = (bp)d_in[1]; P.pwo = (bp)d_in[2]; P.pwin = (bp)d_in[4]; P.pwsp = (bp)d_in[5]; P.pbsp = (bp)d_in[6];
  P.pwout = (bp)d_in[7]; P.pc = (bp)d_in[8]; P.pwmod = (bp)d_in[9]; P.out = (__nv_bfloat16*)d_out;
  make_map(enc, &P.wmod, d_in[9], 6 * DM, DM, 8, 224, CU_TENSOR_MAP_SWIZZLE_NONE);
  make_map(enc, &P.wmods, d_in[9], 6 * DM, DM, 224, 224, CU_TENSOR_MAP_SWIZZLE_NONE);
  make_map(enc, &P.x, d_in[0], DM, SEQ, 64, 128);
  make_map(enc, &P.wqkv, d_in[1], 3 * DM, DM, 64, 64);
  make_map(enc, &P.wo64, d_in[2], DM, DM, 56, 64);
  make_map(enc, &P.wo48, d_in[2], DM, DM, 56, 64);
  make_map(enc, &P.win64, d_in[4], 2 * FH, DM, 64, 64);
  make_map(enc, &P.win48, d_in[4], 2 * FH, DM, 48, 64);
  make_map(enc, &P.wsp, d_in[5], SEQ, SEQ, 64, 128);
  make_map(enc, &P.wout64, d_in[7], DM, FH, 64, 64);
  make_map(enc, &P.wout48, d_in[7], DM, FH, 48, 64);
  fused_kernel<<<132, 384, SMEM_BYTES, cudaStreamPerThread>>>(P);
}
```

```cpp
#include <cuda_runtime.h>
#include <cuda_bf16.h>
#include <cuda.h>
#include <stdint.h>

namespace {

constexpr int SEQ = 2048, DM = 448, FH = 896;
constexpr uint32_t PG = 8192;
constexpr uint32_t MISC = 27 * PG;
constexpr uint32_t OFF_MW = MISC;
constexpr uint32_t OFF_MOD1 = MISC + 3072;
constexpr uint32_t OFF_MOD2 = OFF_MOD1 + 2048;
constexpr uint32_t OFF_GA = OFF_MOD2 + 1792;
constexpr uint32_t OFF_GB = OFF_GA + 224;
constexpr uint32_t OFF_R5 = OFF_GB + 112;
constexpr uint32_t OFF_RED = OFF_R5 + 2048;
constexpr uint32_t OFF_BAR = OFF_RED + 256;
constexpr uint32_t SMEM_BYTES = OFF_BAR + 896;
constexpr uint32_t OFF_RAW1B = 14 * PG;
constexpr uint32_t OFF_XB5_0 = 0;
constexpr uint32_t OFF_XB5_1 = 25 * PG + 5120;
static_assert(SMEM_BYTES <= 232448, "smem");

enum : int {
  B_WK = 0, B_WV, B_WQ, B_WO, B_Z2W  , B_Z1W = B_Z2W + 3  , B_B6 = B_Z1W + 3  , B_ST2 = B_B6 + 3  ,
  B_XB5 = B_ST2 + 2  , B_XB6 = B_XB5 + 2  , B_RAW = B_XB6 + 2  , B_X = B_RAW + 2  , B_A3 = B_X, B_A4 = B_A3 + 7  , B_MW = B_A4 + 14, B_S5F  , B_END1 = B_S5F + 4,
  B_CNT2 = 48, B_STGDONE = B_CNT2, B_MOD2,
  B_CNT4 = 60, B_A4RD = B_CNT4  , B_STG = B_A4RD + 2  , B_KRDY = B_STG + 2  ,
  B_A4E = B_KRDY + 4, B_XRD, B_TURN  , B_END4 = B_TURN + 3,
  B_CNT8 = 84, B_XFREE = B_CNT8, B_KPASS, B_VPASS, B_QPASS, B_ATT, B_Z2PASS, B_Z2C, B_Z1C  , B_S5E = B_Z1C + 3  ,
  B_X5FREE = B_S5E + 4, B_X6FREE, B_KALL, B_VALL, B_XFREE2, B_ATT2, B_S3MMA, B_S3MMA2, B_XST, B_END8,
  B_COUNT = 108,
  PH1 = 128
};
static_assert(B_XB5 >= 12 && B_RAW + 2 <= 24 && B_X5FREE >= 96 && B_END1 <= B_CNT2 && B_END4 <= B_CNT8 && B_END8 <= B_COUNT, "barriers");

constexpr int C_K = 0  , C_O = 256, C_X = 288, C_Z = 320, C_U = 352, C_COUNT = 416;

constexpr int CSTR = 64;
constexpr int MODREP = 16;
struct Small {
  uint32_t epoch, pad[31];
  uint32_t mod[MODREP * 2688];
  uint32_t cnt[C_COUNT * CSTR];
  float2 st2[SEQ];
  uint8_t zs[32 * 1024];
  float2 st1[SEQ * 8];
};
__device__ __align__(1024) Small g_s;
#define g_epoch g_s.epoch
#define g_mod g_s.mod
#define g_cnt g_s.cnt
#define g_st1 g_s.st1
#define g_st2 g_s.st2
__device__ __align__(1024) uint8_t g_kv[16 * 8 * 2 * 16384];
__device__ __align__(1024) __nv_bfloat16 g_o[SEQ * DM];
__device__ __align__(1024) __nv_bfloat16 g_x1[SEQ * DM];
__device__ __align__(1024) __nv_bfloat16 g_u[SEQ * FH];
__device__ __align__(1024) uint8_t g_z2t[32 * FH * 128];

struct Params {
  CUtensorMap wmods, wmod, x, wsp, wqkv, wo64, wo48, win64, win48, wout64, wout48;
  const __nv_bfloat16 *px, *pwqkv, *pwo, *pwin, *pwsp, *pbsp, *pwout, *pc, *pwmod;
  __nv_bfloat16* out;
};

__device__ __forceinline__ uint32_t smem_u32(const void* p) { return (uint32_t)__cvta_generic_to_shared(p); }
__device__ __forceinline__ void mbar_init(uint32_t bar, uint32_t cnt) { asm volatile("mbarrier.init.shared::cta.b64 [%0], %1;" ::"r"(bar), "r"(cnt)); }
__device__ __forceinline__ void mbar_arrive(uint32_t bar) { asm volatile("mbarrier.arrive.shared::cta.b64 _, [%0];" ::"r"(bar) : "memory"); }
__device__ __forceinline__ uint32_t mapa(uint32_t addr, uint32_t cta) { uint32_t r; asm volatile("mapa.shared::cluster.u32 %0, %1, %2;" : "=r"(r) : "r"(addr), "r"(cta)); return r; }
__device__ __forceinline__ void mbar_wait2(uint32_t bar, uint32_t par, int& bud) {
  asm volatile("{\n.reg .pred p;\nWLOOP:\nmbarrier.try_wait.parity.shared::cta.b64 p, [%1], %2;\n@p bra WDONE;\n"
               "add.s32 %0, %0, -1;\nsetp.gt.s32 p, %0, 0;\n@p bra WLOOP;\nWDONE:\n}" : "+r"(bud) : "r"(bar), "r"(par) : "memory");
}
__device__ __forceinline__ void bar_sync(int id, int n) { asm volatile("bar.sync %0, %1;" ::"r"(id), "r"(n) : "memory"); }
__device__ __forceinline__ void bar_arrive(int id, int n) { asm volatile("bar.arrive %0, %1;" ::"r"(id), "r"(n) : "memory"); }
__device__ __forceinline__ void fence_async_smem() { asm volatile("fence.proxy.async.shared::cta;" ::: "memory"); }
__device__ __forceinline__ void fence_async_glob() { asm volatile("fence.proxy.async.global;" ::: "memory"); }
#define ELECT(body) "{\n.reg .pred p;\nelect.sync _|p, 0xffffffff;\n@p " body "\n}"
__device__ __forceinline__ void e_expect(uint32_t bar, uint32_t bytes) { asm volatile(ELECT("mbarrier.arrive.expect_tx.shared::cta.b64 _, [%0], %1;") ::"r"(bar), "r"(bytes) : "memory"); }
__device__ __forceinline__ void e_arrive(uint32_t bar) { __syncwarp(); asm volatile(ELECT("mbarrier.arrive.shared::cta.b64 _, [%0];") ::"r"(bar) : "memory"); }
__device__ __forceinline__ void e_arrive_remote(uint32_t rbar) { asm volatile(ELECT("mbarrier.arrive.shared::cluster.b64 _, [%0];") ::"r"(rbar) : "memory"); }
__device__ __forceinline__ void e_tma2d(uint32_t dst, const CUtensorMap* map, int c0, int c1, uint32_t bar) {
  asm volatile(ELECT("cp.async.bulk.tensor.2d.shared::cluster.global.mbarrier::complete_tx::bytes [%0], [%1, {%3, %4}], [%2];")
               ::"r"(dst), "l"(map), "r"(bar), "r"(c0), "r"(c1) : "memory");
}
__device__ __forceinline__ void e_tma2d_mc(uint32_t dst, const CUtensorMap* map, int c0, int c1, uint32_t bar) {
  asm volatile(ELECT("cp.async.bulk.tensor.2d.shared::cluster.global.mbarrier::complete_tx::bytes.multicast::cluster [%0], [%1, {%3, %4}], [%2], %5;")
               ::"r"(dst), "l"(map), "r"(bar), "r"(c0), "r"(c1), "h"((uint16_t)3) : "memory");
}
__device__ __forceinline__ void e_bulk_ld(uint32_t dst, const void* src, uint32_t bytes, uint32_t bar) {
  asm volatile(ELECT("cp.async.bulk.shared::cluster.global.mbarrier::complete_tx::bytes [%0], [%1], %2, [%3];")
               ::"r"(dst), "l"(src), "r"(bytes), "r"(bar) : "memory");
}
__device__ __forceinline__ void e_bulk_ld_mc(uint32_t dst, const void* src, uint32_t bytes, uint32_t bar) {
  asm volatile(ELECT("cp.async.bulk.shared::cluster.global.mbarrier::complete_tx::bytes.multicast::cluster [%0], [%1], %2, [%3], %4;")
               ::"r"(dst), "l"(src), "r"(bytes), "r"(bar), "h"((uint16_t)3) : "memory");
}
__device__ __forceinline__ void e_bulk_st(void* dst, uint32_t src, uint32_t bytes) {
  asm volatile(ELECT("cp.async.bulk.global.shared::cta.bulk_group [%0], [%1], %2;") ::"l"(dst), "r"(src), "r"(bytes) : "memory");
}
__device__ __forceinline__ void bulk_done() {
  asm volatile("cp.async.bulk.commit_group;" ::: "memory");
  asm volatile("cp.async.bulk.wait_group 0;" ::: "memory");
  __syncwarp();
}
__device__ __forceinline__ void l2_prefetch(const void* p, int bytes, int lane) {
#pragma unroll 1
  for (int o = lane * 128; o < bytes; o += 4096) asm volatile("prefetch.global.L2 [%0];" ::"l"((const uint8_t*)p + o) : "memory");
}
__device__ __forceinline__ void prefetch_map(const CUtensorMap* m) { asm volatile("prefetch.tensormap [%0];" ::"l"(m) : "memory"); }
__device__ __forceinline__ uint32_t ld_acquire(const uint32_t* p) { uint32_t v; asm volatile("ld.acquire.gpu.global.u32 %0, [%1];" : "=r"(v) : "l"(p) : "memory"); return v; }
__device__ __forceinline__ uint32_t ld_relaxed(const uint32_t* p) { uint32_t v; asm volatile("ld.relaxed.gpu.global.u32 %0, [%1];" : "=r"(v) : "l"(p) : "memory"); return v; }
__device__ __forceinline__ uint4 ld_relaxed4(const uint32_t* p) {
  uint4 v; asm volatile("ld.relaxed.gpu.global.v4.u32 {%0,%1,%2,%3}, [%4];" : "=r"(v.x), "=r"(v.y), "=r"(v.z), "=r"(v.w) : "l"(p) : "memory"); return v;
}
__device__ __forceinline__ void st_relaxed(uint32_t* p, uint32_t v) { asm volatile("st.relaxed.gpu.global.u32 [%0], %1;" ::"l"(p), "r"(v) : "memory"); }
__device__ __forceinline__ void e_release(int c) { __syncwarp(); asm volatile(ELECT("red.release.gpu.global.add.u32 [%0], 1;") ::"l"(&g_cnt[c * CSTR]) : "memory"); }
__device__ __forceinline__ void e_publish(int c) { bulk_done(); fence_async_glob(); e_release(c); }
__device__ __forceinline__ bool reached(int c, uint32_t target) { return (int)(ld_acquire(&g_cnt[c * CSTR]) - target) >= 0; }
__device__ __forceinline__ void ldsm4(uint32_t* r, uint32_t addr) {
  asm volatile("ldmatrix.sync.aligned.m8n8.x4.shared.b16 {%0,%1,%2,%3}, [%4];" : "=r"(r[0]), "=r"(r[1]), "=r"(r[2]), "=r"(r[3]) : "r"(addr) : "memory");
}
__device__ __forceinline__ void stsm4(uint32_t addr, uint32_t r0, uint32_t r1, uint32_t r2, uint32_t r3) {
  asm volatile("stmatrix.sync.aligned.m8n8.x4.shared.b16 [%0], {%1,%2,%3,%4};" ::"r"(addr), "r"(r0), "r"(r1), "r"(r2), "r"(r3) : "memory");
}
__device__ __forceinline__ void stsm2(uint32_t addr, uint32_t r0, uint32_t r1) {
  asm volatile("stmatrix.sync.aligned.m8n8.x2.shared.b16 [%0], {%1,%2};" ::"r"(addr), "r"(r0), "r"(r1) : "memory");
}
__device__ __forceinline__ void stsm4t(uint32_t addr, uint32_t r0, uint32_t r1, uint32_t r2, uint32_t r3) {
  asm volatile("stmatrix.sync.aligned.m8n8.x4.trans.shared.b16 [%0], {%1,%2,%3,%4};" ::"r"(addr), "r"(r0), "r"(r1), "r"(r2), "r"(r3) : "memory");
}
__device__ __forceinline__ uint4 lds128(uint32_t addr) {
  uint4 v; asm volatile("ld.shared.v4.u32 {%0,%1,%2,%3}, [%4];" : "=r"(v.x), "=r"(v.y), "=r"(v.z), "=r"(v.w) : "r"(addr) : "memory"); return v;
}
__device__ __forceinline__ float2 lds64f(uint32_t addr) {
  float2 v; asm volatile("ld.shared.v2.f32 {%0,%1}, [%2];" : "=f"(v.x), "=f"(v.y) : "r"(addr) : "memory"); return v;
}
__device__ __forceinline__ void sts32(uint32_t addr, uint32_t v) { asm volatile("st.shared.u32 [%0], %1;" ::"r"(addr), "r"(v) : "memory"); }
__device__ __forceinline__ void sts32f(uint32_t addr, float v) { asm volatile("st.shared.f32 [%0], %1;" ::"r"(addr), "f"(v) : "memory"); }
__device__ __forceinline__ uint32_t lds32(uint32_t addr) { uint32_t v; asm volatile("ld.shared.u32 %0, [%1];" : "=r"(v) : "r"(addr) : "memory"); return v; }
__device__ __forceinline__ float lds32f(uint32_t addr) { float v; asm volatile("ld.shared.f32 %0, [%1];" : "=f"(v) : "r"(addr) : "memory"); return v; }
__device__ __forceinline__ void sts128(uint32_t addr, uint4 v) { asm volatile("st.shared.v4.u32 [%0], {%1,%2,%3,%4};" ::"r"(addr), "r"(v.x), "r"(v.y), "r"(v.z), "r"(v.w) : "memory"); }
__device__ __forceinline__ void st_async4(uint32_t raddr, uint32_t a, uint32_t b, uint32_t c, uint32_t d, uint32_t rbar) {
  asm volatile("st.async.shared::cluster.mbarrier::complete_tx::bytes.v4.b32 [%0], {%1,%2,%3,%4}, [%5];" ::"r"(raddr), "r"(a), "r"(b), "r"(c), "r"(d), "r"(rbar) : "memory");
}
__device__ __forceinline__ void st_async2(uint32_t raddr, uint32_t a, uint32_t b, uint32_t rbar) {
  asm volatile("st.async.shared::cluster.mbarrier::complete_tx::bytes.v2.b32 [%0], {%1,%2}, [%3];" ::"r"(raddr), "r"(a), "r"(b), "r"(rbar) : "memory");
}
__device__ __forceinline__ uint32_t pack2(float lo, float hi) { uint32_t r; asm("cvt.rn.bf16x2.f32 %0, %1, %2;" : "=r"(r) : "f"(hi), "f"(lo)); return r; }
__device__ __forceinline__ float bf_lo(uint32_t w) { return __uint_as_float(w << 16); }
__device__ __forceinline__ float bf_hi(uint32_t w) { return __uint_as_float(w & 0xFFFF0000u); }
__device__ __forceinline__ uint32_t hfma2(uint32_t a, uint32_t b, uint32_t c) { uint32_t r; asm("fma.rn.bf16x2 %0, %1, %2, %3;" : "=r"(r) : "r"(a), "r"(b), "r"(c)); return r; }
__device__ __forceinline__ uint32_t hmul2(uint32_t a, uint32_t b) { uint32_t r; asm("mul.rn.bf16x2 %0, %1, %2;" : "=r"(r) : "r"(a), "r"(b)); return r; }
__device__ __forceinline__ uint32_t hsub2(uint32_t a, uint32_t b) { uint32_t r; asm("sub.rn.bf16x2 %0, %1, %2;" : "=r"(r) : "r"(a), "r"(b)); return r; }
__device__ __forceinline__ float ex2v(float x) { float r; asm volatile("ex2.approx.ftz.f32 %0, %1;" : "=f"(r) : "f"(x)); return r; }
__device__ __forceinline__ void stg128(void* p, uint4 v) { asm volatile("st.global.v4.u32 [%0], {%1,%2,%3,%4};" ::"l"(p), "r"(v.x), "r"(v.y), "r"(v.z), "r"(v.w) : "memory"); }
__device__ __forceinline__ uint32_t hadd2(uint32_t a, uint32_t b) { uint32_t r; asm("add.rn.bf16x2 %0, %1, %2;" : "=r"(r) : "r"(a), "r"(b)); return r; }
__device__ __forceinline__ float ex2(float x) { float r; asm("ex2.approx.ftz.f32 %0, %1;" : "=f"(r) : "f"(x)); return r; }
__device__ __forceinline__ float gelu_h(float y) {
  float u = y * fmaf(8.f * 0.0356774081f, y * y, 2.f * 0.7978845608f), t;
  asm("tanh.approx.f32 %0, %1;" : "=f"(t) : "f"(u));
  return fmaf(y, t, y);
}
__device__ __forceinline__ float quad_sum(float v) { v += __shfl_xor_sync(~0u, v, 1); v += __shfl_xor_sync(~0u, v, 2); return v; }
__device__ __forceinline__ float quad_max(float v) { v = fmaxf(v, __shfl_xor_sync(~0u, v, 1)); v = fmaxf(v, __shfl_xor_sync(~0u, v, 2)); return v; }
__device__ __forceinline__ void rowsum_mma(float* c, const uint32_t* a) {
  asm volatile("mma.sync.aligned.m16n8k16.row.col.f32.bf16.bf16.f32 {%0,%1,%2,%3}, {%4,%5,%6,%7}, {%8,%8}, {%0,%1,%2,%3};"
               : "+f"(c[0]), "+f"(c[1]), "+f"(c[2]), "+f"(c[3]) : "r"(a[0]), "r"(a[1]), "r"(a[2]), "r"(a[3]), "r"(0x3F803F80u));
}
__device__ __forceinline__ void wg_fence() { asm volatile("wgmma.fence.sync.aligned;" ::: "memory"); }
__device__ __forceinline__ void wg_commit() { asm volatile("wgmma.commit_group.sync.aligned;" ::: "memory"); }
template <int N> __device__ __forceinline__ void wg_wait() { asm volatile("wgmma.wait_group.sync.aligned %0;" ::"n"(N) : "memory"); }
constexpr uint32_t SMEM0 = 1024;
__device__ __forceinline__ uint64_t desc(uint32_t rt16, uint32_t off, uint32_t lbo) {
  return (uint64_t)(rt16 + (((SMEM0 + off) >> 4) | ((lbo >> 4) << 16))) | ((uint64_t)0x40000040u << 32);
}
template <int N> __device__ __forceinline__ void keep(float* d) {
#pragma unroll
  for (int i = 0; i < N; i++) asm volatile("" : "+f"(d[i]));
}

template <int TB> __device__ __forceinline__ void wg_rs32(float* d, const uint32_t* a, uint64_t db, int sd) {
  asm volatile("{\n.reg .pred p;\nsetp.ne.b32 p, %21, 0;\n"
    "wgmma.mma_async.sync.aligned.m64n32k16.f32.bf16.bf16 {%0, %1, %2, %3, %4, %5, %6, %7, %8, %9, %10, %11, %12, %13, %14, %15}, {%16, %17, %18, %19}, %20, p, 1, 1, %22;\n}"
    : "+f"(d[0]), "+f"(d[1]), "+f"(d[2]), "+f"(d[3]), "+f"(d[4]), "+f"(d[5]), "+f"(d[6]), "+f"(d[7]), "+f"(d[8]), "+f"(d[9]), "+f"(d[10]), "+f"(d[11]), "+f"(d[12]), "+f"(d[13]), "+f"(d[14]), "+f"(d[15])
    : "r"(a[0]), "r"(a[1]), "r"(a[2]), "r"(a[3]), "l"(db), "r"(sd), "n"(TB));
}
template <int TB> __device__ __forceinline__ void wg_rs56(float* d, const uint32_t* a, uint64_t db, int sd) {
  asm volatile("{\n.reg .pred p;\nsetp.ne.b32 p, %33, 0;\n"
    "wgmma.mma_async.sync.aligned.m64n56k16.f32.bf16.bf16 {%0, %1, %2, %3, %4, %5, %6, %7, %8, %9, %10, %11, %12, %13, %14, %15, %16, %17, %18, %19, %20, %21, %22, %23, %24, %25, %26, %27}, {%28, %29, %30, %31}, %32, p, 1, 1, %34;\n}"
    : "+f"(d[0]), "+f"(d[1]), "+f"(d[2]), "+f"(d[3]), "+f"(d[4]), "+f"(d[5]), "+f"(d[6]), "+f"(d[7]), "+f"(d[8]), "+f"(d[9]), "+f"(d[10]), "+f"(d[11]), "+f"(d[12]), "+f"(d[13]), "+f"(d[14]), "+f"(d[15]), "+f"(d[16]), "+f"(d[17]), "+f"(d[18]), "+f"(d[19]), "+f"(d[20]), "+f"(d[21]), "+f"(d[22]), "+f"(d[23]), "+f"(d[24]), "+f"(d[25]), "+f"(d[26]), "+f"(d[27])
    : "r"(a[0]), "r"(a[1]), "r"(a[2]), "r"(a[3]), "l"(db), "r"(sd), "n"(TB));
}
template <int TB> __device__ __forceinline__ void wg_rs64(float* d, const uint32_t* a, uint64_t db, int sd) {
  asm volatile("{\n.reg .pred p;\nsetp.ne.b32 p, %37, 0;\n"
    "wgmma.mma_async.sync.aligned.m64n64k16.f32.bf16.bf16 {%0, %1, %2, %3, %4, %5, %6, %7, %8, %9, %10, %11, %12, %13, %14, %15, %16, %17, %18, %19, %20, %21, %22, %23, %24, %25, %26, %27, %28, %29, %30, %31}, {%32, %33, %34, %35}, %36, p, 1, 1, %38;\n}"
    : "+f"(d[0]), "+f"(d[1]), "+f"(d[2]), "+f"(d[3]), "+f"(d[4]), "+f"(d[5]), "+f"(d[6]), "+f"(d[7]), "+f"(d[8]), "+f"(d[9]), "+f"(d[10]), "+f"(d[11]), "+f"(d[12]), "+f"(d[13]), "+f"(d[14]), "+f"(d[15]), "+f"(d[16]), "+f"(d[17]), "+f"(d[18]), "+f"(d[19]), "+f"(d[20]), "+f"(d[21]), "+f"(d[22]), "+f"(d[23]), "+f"(d[24]), "+f"(d[25]), "+f"(d[26]), "+f"(d[27]), "+f"(d[28]), "+f"(d[29]), "+f"(d[30]), "+f"(d[31])
    : "r"(a[0]), "r"(a[1]), "r"(a[2]), "r"(a[3]), "l"(db), "r"(sd), "n"(TB));
}
template <int TB> __device__ __forceinline__ void wg_rs112(float* d, const uint32_t* a, uint64_t db, int sd) {
  asm volatile("{\n.reg .pred p;\nsetp.ne.b32 p, %61, 0;\n"
    "wgmma.mma_async.sync.aligned.m64n112k16.f32.bf16.bf16 {%0, %1, %2, %3, %4, %5, %6, %7, %8, %9, %10, %11, %12, %13, %14, %15, %16, %17, %18, %19, %20, %21, %22, %23, %24, %25, %26, %27, %28, %29, %30, %31, %32, %33, %34, %35, %36, %37, %38, %39, %40, %41, %42, %43, %44, %45, %46, %47, %48, %49, %50, %51, %52, %53, %54, %55}, {%56, %57, %58, %59}, %60, p, 1, 1, %62;\n}"
    : "+f"(d[0]), "+f"(d[1]), "+f"(d[2]), "+f"(d[3]), "+f"(d[4]), "+f"(d[5]), "+f"(d[6]), "+f"(d[7]), "+f"(d[8]), "+f"(d[9]), "+f"(d[10]), "+f"(d[11]), "+f"(d[12]), "+f"(d[13]), "+f"(d[14]), "+f"(d[15]), "+f"(d[16]), "+f"(d[17]), "+f"(d[18]), "+f"(d[19]), "+f"(d[20]), "+f"(d[21]), "+f"(d[22]), "+f"(d[23]), "+f"(d[24]), "+f"(d[25]), "+f"(d[26]), "+f"(d[27]), "+f"(d[28]), "+f"(d[29]), "+f"(d[30]), "+f"(d[31]), "+f"(d[32]), "+f"(d[33]), "+f"(d[34]), "+f"(d[35]), "+f"(d[36]), "+f"(d[37]), "+f"(d[38]), "+f"(d[39]), "+f"(d[40]), "+f"(d[41]), "+f"(d[42]), "+f"(d[43]), "+f"(d[44]), "+f"(d[45]), "+f"(d[46]), "+f"(d[47]), "+f"(d[48]), "+f"(d[49]), "+f"(d[50]), "+f"(d[51]), "+f"(d[52]), "+f"(d[53]), "+f"(d[54]), "+f"(d[55])
    : "r"(a[0]), "r"(a[1]), "r"(a[2]), "r"(a[3]), "l"(db), "r"(sd), "n"(TB));
}
template <int TB> __device__ __forceinline__ void wg_rs192(float* d, const uint32_t* a, uint64_t db, int sd) {
  asm volatile("{\n.reg .pred p;\nsetp.ne.b32 p, %101, 0;\n"
    "wgmma.mma_async.sync.aligned.m64n192k16.f32.bf16.bf16 {%0, %1, %2, %3, %4, %5, %6, %7, %8, %9, %10, %11, %12, %13, %14, %15, %16, %17, %18, %19, %20, %21, %22, %23, %24, %25, %26, %27, %28, %29, %30, %31, %32, %33, %34, %35, %36, %37, %38, %39, %40, %41, %42, %43, %44, %45, %46, %47, %48, %49, %50, %51, %52, %53, %54, %55, %56, %57, %58, %59, %60, %61, %62, %63, %64, %65, %66, %67, %68, %69, %70, %71, %72, %73, %74, %75, %76, %77, %78, %79, %80, %81, %82, %83, %84, %85, %86, %87, %88, %89, %90, %91, %92, %93, %94, %95}, {%96, %97, %98, %99}, %100, p, 1, 1, %102;\n}"
    : "+f"(d[0]), "+f"(d[1]), "+f"(d[2]), "+f"(d[3]), "+f"(d[4]), "+f"(d[5]), "+f"(d[6]), "+f"(d[7]), "+f"(d[8]), "+f"(d[9]), "+f"(d[10]), "+f"(d[11]), "+f"(d[12]), "+f"(d[13]), "+f"(d[14]), "+f"(d[15]), "+f"(d[16]), "+f"(d[17]), "+f"(d[18]), "+f"(d[19]), "+f"(d[20]), "+f"(d[21]), "+f"(d[22]), "+f"(d[23]), "+f"(d[24]), "+f"(d[25]), "+f"(d[26]), "+f"(d[27]), "+f"(d[28]), "+f"(d[29]), "+f"(d[30]), "+f"(d[31]), "+f"(d[32]), "+f"(d[33]), "+f"(d[34]), "+f"(d[35]), "+f"(d[36]), "+f"(d[37]), "+f"(d[38]), "+f"(d[39]), "+f"(d[40]), "+f"(d[41]), "+f"(d[42]), "+f"(d[43]), "+f"(d[44]), "+f"(d[45]), "+f"(d[46]), "+f"(d[47]), "+f"(d[48]), "+f"(d[49]), "+f"(d[50]), "+f"(d[51]), "+f"(d[52]), "+f"(d[53]), "+f"(d[54]), "+f"(d[55]), "+f"(d[56]), "+f"(d[57]), "+f"(d[58]), "+f"(d[59]), "+f"(d[60]), "+f"(d[61]), "+f"(d[62]), "+f"(d[63]), "+f"(d[64]), "+f"(d[65]), "+f"(d[66]), "+f"(d[67]), "+f"(d[68]), "+f"(d[69]), "+f"(d[70]), "+f"(d[71]), "+f"(d[72]), "+f"(d[73]), "+f"(d[74]), "+f"(d[75]), "+f"(d[76]), "+f"(d[77]), "+f"(d[78]), "+f"(d[79]), "+f"(d[80]), "+f"(d[81]), "+f"(d[82]), "+f"(d[83]), "+f"(d[84]), "+f"(d[85]), "+f"(d[86]), "+f"(d[87]), "+f"(d[88]), "+f"(d[89]), "+f"(d[90]), "+f"(d[91]), "+f"(d[92]), "+f"(d[93]), "+f"(d[94]), "+f"(d[95])
    : "r"(a[0]), "r"(a[1]), "r"(a[2]), "r"(a[3]), "l"(db), "r"(sd), "n"(TB));
}
template <int TB> __device__ __forceinline__ void wg_rs232(float* d, const uint32_t* a, uint64_t db, int sd) {
  asm volatile("{\n.reg .pred p;\nsetp.ne.b32 p, %121, 0;\n"
    "wgmma.mma_async.sync.aligned.m64n232k16.f32.bf16.bf16 {%0, %1, %2, %3, %4, %5, %6, %7, %8, %9, %10, %11, %12, %13, %14, %15, %16, %17, %18, %19, %20, %21, %22, %23, %24, %25, %26, %27, %28, %29, %30, %31, %32, %33, %34, %35, %36, %37, %38, %39, %40, %41, %42, %43, %44, %45, %46, %47, %48, %49, %50, %51, %52, %53, %54, %55, %56, %57, %58, %59, %60, %61, %62, %63, %64, %65, %66, %67, %68, %69, %70, %71, %72, %73, %74, %75, %76, %77, %78, %79, %80, %81, %82, %83, %84, %85, %86, %87, %88, %89, %90, %91, %92, %93, %94, %95, %96, %97, %98, %99, %100, %101, %102, %103, %104, %105, %106, %107, %108, %109, %110, %111, %112, %113, %114, %115}, {%116, %117, %118, %119}, %120, p, 1, 1, %122;\n}"
    : "+f"(d[0]), "+f"(d[1]), "+f"(d[2]), "+f"(d[3]), "+f"(d[4]), "+f"(d[5]), "+f"(d[6]), "+f"(d[7]), "+f"(d[8]), "+f"(d[9]), "+f"(d[10]), "+f"(d[11]), "+f"(d[12]), "+f"(d[13]), "+f"(d[14]), "+f"(d[15]), "+f"(d[16]), "+f"(d[17]), "+f"(d[18]), "+f"(d[19]), "+f"(d[20]), "+f"(d[21]), "+f"(d[22]), "+f"(d[23]), "+f"(d[24]), "+f"(d[25]), "+f"(d[26]), "+f"(d[27]), "+f"(d[28]), "+f"(d[29]), "+f"(d[30]), "+f"(d[31]), "+f"(d[32]), "+f"(d[33]), "+f"(d[34]), "+f"(d[35]), "+f"(d[36]), "+f"(d[37]), "+f"(d[38]), "+f"(d[39]), "+f"(d[40]), "+f"(d[41]), "+f"(d[42]), "+f"(d[43]), "+f"(d[44]), "+f"(d[45]), "+f"(d[46]), "+f"(d[47]), "+f"(d[48]), "+f"(d[49]), "+f"(d[50]), "+f"(d[51]), "+f"(d[52]), "+f"(d[53]), "+f"(d[54]), "+f"(d[55]), "+f"(d[56]), "+f"(d[57]), "+f"(d[58]), "+f"(d[59]), "+f"(d[60]), "+f"(d[61]), "+f"(d[62]), "+f"(d[63]), "+f"(d[64]), "+f"(d[65]), "+f"(d[66]), "+f"(d[67]), "+f"(d[68]), "+f"(d[69]), "+f"(d[70]), "+f"(d[71]), "+f"(d[72]), "+f"(d[73]), "+f"(d[74]), "+f"(d[75]), "+f"(d[76]), "+f"(d[77]), "+f"(d[78]), "+f"(d[79]), "+f"(d[80]), "+f"(d[81]), "+f"(d[82]), "+f"(d[83]), "+f"(d[84]), "+f"(d[85]), "+f"(d[86]), "+f"(d[87]), "+f"(d[88]), "+f"(d[89]), "+f"(d[90]), "+f"(d[91]), "+f"(d[92]), "+f"(d[93]), "+f"(d[94]), "+f"(d[95]), "+f"(d[96]), "+f"(d[97]), "+f"(d[98]), "+f"(d[99]), "+f"(d[100]), "+f"(d[101]), "+f"(d[102]), "+f"(d[103]), "+f"(d[104]), "+f"(d[105]), "+f"(d[106]), "+f"(d[107]), "+f"(d[108]), "+f"(d[109]), "+f"(d[110]), "+f"(d[111]), "+f"(d[112]), "+f"(d[113]), "+f"(d[114]), "+f"(d[115])
    : "r"(a[0]), "r"(a[1]), "r"(a[2]), "r"(a[3]), "l"(db), "r"(sd), "n"(TB));
}
template <int TB> __device__ __forceinline__ void wg_ss56(float* d, uint64_t da, uint64_t db, int sd) {
  asm volatile("{\n.reg .pred p;\nsetp.ne.b32 p, %30, 0;\n"
    "wgmma.mma_async.sync.aligned.m64n56k16.f32.bf16.bf16 {%0, %1, %2, %3, %4, %5, %6, %7, %8, %9, %10, %11, %12, %13, %14, %15, %16, %17, %18, %19, %20, %21, %22, %23, %24, %25, %26, %27}, %28, %29, p, 1, 1, 0, %31;\n}"
    : "+f"(d[0]), "+f"(d[1]), "+f"(d[2]), "+f"(d[3]), "+f"(d[4]), "+f"(d[5]), "+f"(d[6]), "+f"(d[7]), "+f"(d[8]), "+f"(d[9]), "+f"(d[10]), "+f"(d[11]), "+f"(d[12]), "+f"(d[13]), "+f"(d[14]), "+f"(d[15]), "+f"(d[16]), "+f"(d[17]), "+f"(d[18]), "+f"(d[19]), "+f"(d[20]), "+f"(d[21]), "+f"(d[22]), "+f"(d[23]), "+f"(d[24]), "+f"(d[25]), "+f"(d[26]), "+f"(d[27])
    : "l"(da), "l"(db), "r"(sd), "n"(TB));
}


__device__ __forceinline__ int perm448(int k) { return (k >> 5) * 32 + ((k & 7) >> 1) * 8 + ((k >> 4) & 1) * 4 + ((k >> 3) & 1) * 2 + (k & 1); }
__device__ __forceinline__ int perm64(int k) { return ((k & 7) >> 1) * 16 + (k >> 4) * 4 + ((k >> 3) & 1) * 2 + (k & 1); }

__device__ __forceinline__ float rcp(float x) { float r; asm("rcp.approx.ftz.f32 %0, %1;" : "=f"(r) : "f"(x)); return r; }
__device__ __forceinline__ float silu_bf(float c) { return bf_lo(pack2(c * rcp(1.f + ex2(-1.4426950408889634f * c)), 0.f)); }
__device__ __forceinline__ void fma8(float* acc, uint4 w, float s) {
  acc[0] = fmaf(bf_lo(w.x), s, acc[0]); acc[1] = fmaf(bf_hi(w.x), s, acc[1]);
  acc[2] = fmaf(bf_lo(w.y), s, acc[2]); acc[3] = fmaf(bf_hi(w.y), s, acc[3]);
  acc[4] = fmaf(bf_lo(w.z), s, acc[4]); acc[5] = fmaf(bf_hi(w.z), s, acc[5]);
  acc[6] = fmaf(bf_lo(w.w), s, acc[6]); acc[7] = fmaf(bf_hi(w.w), s, acc[7]);
}
__device__ __forceinline__ float warp_red8(float* v, int lane) {
  bool b4 = lane & 16, b3 = lane & 8, b2 = lane & 4;
  float t[4];
#pragma unroll
  for (int i = 0; i < 4; i++) { float keepv = b4 ? v[i + 4] : v[i], send = b4 ? v[i] : v[i + 4]; t[i] = keepv + __shfl_xor_sync(~0u, send, 16); }
  float u[2];
#pragma unroll
  for (int i = 0; i < 2; i++) { float keepv = b3 ? t[i + 2] : t[i], send = b3 ? t[i] : t[i + 2]; u[i] = keepv + __shfl_xor_sync(~0u, send, 8); }
  float keepv = b2 ? u[1] : u[0], send = b2 ? u[0] : u[1];
  float r = keepv + __shfl_xor_sync(~0u, send, 4);
  r += __shfl_xor_sync(~0u, r, 2);
  r += __shfl_xor_sync(~0u, r, 1);
  return r;
}

template <int NT> __device__ __forceinline__ void stage_rows(const uint32_t* w, uint32_t stg, int lane) {
  const uint32_t sa = stg + (lane & 15) * (NT * 16) + (lane >> 4) * 16;
#pragma unroll
  for (int t = 0; t + 1 < NT; t += 2) stsm4(sa + t * 16, w[2 * t], w[2 * t + 1], w[2 * t + 2], w[2 * t + 3]);
  if (NT & 1) stsm2(sa + (NT - 1) * 16, w[2 * NT - 2], w[2 * NT - 1]);
}
template <int NT> __device__ __forceinline__ void store_cm(const uint32_t* w, __nv_bfloat16* p) {
#pragma unroll
  for (int t = 0; t < NT; t++) { *(uint32_t*)(p + t * 512) = w[2 * t]; *(uint32_t*)(p + t * 512 + 64) = w[2 * t + 1]; }
}
template <int NT> __device__ __forceinline__ void store_rows(const uint32_t* w, uint32_t stg, __nv_bfloat16* gp, int pitch, int lane) {
  stage_rows<NT>(w, stg, lane);
  __syncwarp();
  {
    const int r = (lane * 37) >> 8, c = lane - 7 * r;
    gp += r * pitch + c * 8;
    if (lane < 28) {
#pragma unroll
      for (int k = 0; k < 4; k++) stg128(gp + 4 * k * pitch, lds128(stg + lane * 16 + k * 448));
    }
  }
}
__device__ __forceinline__ int st2pos(int h) { return ((h >> 4) * 16 + (h & 1) * 8 + ((h >> 1) & 7)) * 64; }
__device__ __forceinline__ uint32_t mod_bad(uint4 v, uint32_t tag) { return (v.x ^ tag) | (v.y ^ tag) | (v.z ^ tag) | (v.w ^ tag); }
__device__ __forceinline__ void put_mod4(uint32_t base, int i, uint4 v, uint32_t s2) {
  const bool isc = i >= 112;
  const float one = isc ? 1.f : 0.f;
  const int k = (isc ? i - 112 : i) * 4;
  base += (isc ? 0 : 896) + perm448(k) * 2;
  sts32(base, hmul2(pack2(bf_lo(v.x) + one, bf_lo(v.y) + one), s2));
  sts32(base + 16, hmul2(pack2(bf_lo(v.z) + one, bf_lo(v.w) + one), s2));
}

__host__ __device__ constexpr uint32_t bar_count(int i) { return i >= B_CNT8 ? 8 : i >= B_CNT4 ? 4 : i >= B_CNT2 ? 2 : 1; }
constexpr uint32_t WE(int wait, int p0, int p1, int full, int c, int type, int add, int n) {
  return (uint32_t)wait | p0 << 8 | p1 << 13 | full << 18 | c << 22 | type << 25 | add << 27 | (uint32_t)n << 29;
}
__constant__ uint32_t c_wprog[21] = {
  WE(B_VALL, 20, 21, B_WO, 4, 1, 0, 7), WE(0, 22, 23, B_WO, 5, 1, 0, 0), WE(0, 24, 25, B_WO, 6, 1, 0, 0),
  WE(B_QPASS, 0, 1, B_WO, 0, 1, 0, 0), WE(0, 2, 3, B_WO, 1, 1, 0, 0), WE(0, 4, 5, B_WO, 2, 1, 0, 0), WE(0, 6, 7, B_WO, 3, 1, 0, 0),
  WE(PH1 + B_A3 + 6, 16, 17, B_Z2W, 0, 2, 2, 3), WE(0, 18, 19, B_Z2W, 1, 2, 2, 0), WE(B_XST, 15, 26, B_Z2W, 2, 2, 2, 0),
  WE(B_A4 + 5, 20, 21, B_Z2W + 1, 3, 2, 2, 3), WE(0, 22, 23, B_Z2W + 1, 4, 2, 2, 0), WE(0, 24, 25, B_Z2W + 1, 5, 2, 2, 0),
  WE(B_A4E, 0, 1, B_Z2W + 2, 6, 2, 2, 1),
  WE(B_A4RD, 4, 5, B_Z1W, 0, 2, 0, 2), WE(B_A4RD + 1, 6, 14, B_Z1W, 1, 2, 0, 0),
  WE(0, 9, 10, B_Z1W + 1, 2, 2, 0, 2), WE(0, 11, 12, B_Z1W + 1, 3, 2, 0, 0),
  WE(B_Z2C, 16, 17, B_Z1W + 2, 4, 2, 0, 3), WE(0, 18, 19, B_Z1W + 2, 5, 2, 0, 0), WE(B_Z2PASS, 0, 1, B_Z1W + 2, 6, 2, 0, 0)};

__global__ void __cluster_dims__(2, 1, 1) __launch_bounds__(384, 1) fused_kernel(const __grid_constant__ Params P) {
  extern __shared__ __align__(1024) uint8_t smem_raw[];
  const uint32_t sb = smem_u32(smem_raw);
  const int tid = threadIdx.x, lane = tid & 31, warp = __shfl_sync(~0u, tid >> 5, 0);
  const int b = blockIdx.x, rb = b >> 3, c8 = b & 7, cb4 = c8 >> 1, kh = c8 & 1;
  const int h3 = 2 * rb + (cb4 & 1), c4 = 2 * (cb4 >> 1) + kh;
  const int rb1 = 2 * (b >> 4) + kh, j1 = (b >> 1) & 7, b1 = rb1 * 8 + j1;
  const uint32_t peer = kh ^ 1;
  int bud = 1 << 20;
  auto BAR = [&](int i) { return sb + OFF_BAR + 8u * i; };
  auto PAGE = [&](int i) { return sb + PG * i; };
  auto mbar_wait = [&](uint32_t bar, uint32_t par = 0) { mbar_wait2(bar, par, bud); };
  auto poll = [&](int c, uint32_t target) { while (!__all_sync(~0u, reached(c, target)) && --bud > 0) {} fence_async_glob(); };

  if (blockIdx.x >= 128) {
    float* tab = (float*)(smem_raw + 200704);
    const int rg = min(tid / 56, 5), cg = tid - 56 * (tid / 56), col0 = 448 * (b - 126);
    if (tid == 0) { mbar_init(BAR(0), 1); fence_async_smem(); }
    __syncthreads();
    const uint32_t tg = (ld_relaxed(&g_epoch) + 1) << 16;
    float acc[8] = {0, 0, 0, 0, 0, 0, 0, 0};
#pragma unroll 1
    for (int h = 0; h < 2; h++) {
      if (warp == 0) {
        e_expect(BAR(0), 200704);
        e_tma2d(sb, &P.wmods, col0, 224 * h, BAR(0));
        e_tma2d(sb + 100352, &P.wmods, col0 + 224, 224 * h, BAR(0));
      }
      if (tid < 224) tab[tid] = silu_bf(bf_lo(__ldg((const uint16_t*)P.pc + 224 * h + tid)));
      __syncthreads();
      mbar_wait(BAR(0), h);
#pragma unroll 2
      for (int k = rg; k < 224; k += 6) fma8(acc, lds128(sb + (cg >= 28 ? 100352 - 448 : 0) + k * 448 + cg * 16), tab[k]);
      __syncthreads();
    }
    if (tid < 336) {
#pragma unroll
      for (int i = 0; i < 8; i++) tab[512 + rg * 448 + cg * 8 + i] = acc[i];
    }
    __syncthreads();
    for (int c = tid; c < 448; c += 384) {
      float v = 0.f;
#pragma unroll
      for (int i = 0; i < 6; i++) v += tab[512 + i * 448 + c];
#pragma unroll 1
      for (int r = 0; r < MODREP; r++) st_relaxed(&g_mod[r * 2688 + col0 + c], (pack2(v, 0.f) & 0xFFFFu) | tg);
    }
    return;
  }
  if ((sb & 0xFFFFFFu) != SMEM0) bud = 0;
  uint32_t ep = 0;
  if (warp <= 8) {
    if (lane == 0) {
      const uint32_t cnt = bar_count(12 * warp);
#pragma unroll
      for (int i = 0; i < 12; i++) mbar_init(BAR(12 * warp + i), cnt);
      asm volatile("fence.mbarrier_init.release.cluster;" ::: "memory");
    }
    __syncwarp();
    if (warp == 1) {
#pragma unroll
      for (int i = 0; i < 6; i++) e_expect(BAR(B_XB5 + i), i < 2 ? 14336 : i < 4 ? 7168 : 4096);
    }
    if (warp == 8) {
      asm volatile(ELECT("mbarrier.expect_tx.relaxed.cta.shared::cta.b64 [%0], %1;") ::"r"(BAR(B_KALL)), "r"(min(rb1, 2) * 16384) : "memory");
      asm volatile(ELECT("mbarrier.expect_tx.relaxed.cta.shared::cta.b64 [%0], %1;") ::"r"(BAR(B_VALL)), "r"(min(rb1, 2) * 16384) : "memory");
    }
    bar_arrive(10, 384);
    bar_sync(6, 288);
  }
  auto cluster_wait = [&]() { asm volatile("barrier.cluster.wait.acquire.aligned;" ::: "memory"); };
  auto cluster_arrive = [&]() { asm volatile("barrier.cluster.arrive.relaxed.aligned;" ::: "memory"); };

  if (warp >= 8) {
    asm volatile("setmaxnreg.dec.sync.aligned.u32 56;");
    auto rows_mc = [&](const __nv_bfloat16* src, int page, int bar, int par) {
#pragma unroll 1
      for (int c = par; c < 7; c += 2) e_bulk_ld_mc(PAGE(page + c), src + c * 4096, 8192, BAR(bar + c));
    };
    const int a = warp - 10, hh = 2 * rb + a;
    if (warp > 8) {
      const int t96 = tid - 288;
      {
        uint16_t cc[5];
#pragma unroll
        for (int q = 0; q < 5; q++) cc[q] = t96 + 96 * q < 448 ? __ldg((const uint16_t*)P.pc + t96 + 96 * q) : (uint16_t)0;
        const uint32_t e0 = ld_relaxed(&g_epoch);
        if (warp == 9 && lane < 10) prefetch_map(&P.wmod + lane);
        cluster_arrive();
        bar_sync(10, 384);
        mbar_wait(BAR(B_MW));
        float acc[8] = {0, 0, 0, 0, 0, 0, 0, 0};
#pragma unroll
        for (int q = 0; q < 5; q++) fma8(acc, lds128(sb + OFF_MW + min(t96 + 96 * q, 447) * 16), silu_bf(bf_lo(cc[q])));
        ep = __shfl_sync(~0u, e0, 0) + 1;
        const float r = warp_red8(acc, lane);
        if (!(lane & 3)) sts32f(sb + OFF_RED + (warp - 9) * 32 + lane, r);
        bar_sync(9, 96);
        if (b < 112) {
          const uint32_t red = sb + OFF_RED + (t96 & 7) * 4;
          const uint32_t v = (pack2(lds32f(red) + lds32f(red + 32) + lds32f(red + 64), 0.f) & 0xFFFFu) | (ep << 16);
#pragma unroll 1
          for (int r = t96 >> 3; r < MODREP; r += 12) st_relaxed(&g_mod[r * 2688 + 8 * b + (t96 & 7)], v);
        }
      }
#pragma unroll 1
      for (int st = 0; st < 3; st++) {
        if (st != 1) {
          if (st && warp == 9) break;
          mbar_wait(BAR(st ? B_WO : B_X + 6));
          bool first = !st;
          const uint32_t* gm = g_mod + rb * 2688;
          const int nt = st ? 64 : 96, ni = st ? 265 : 223;
#pragma unroll 1
          for (int i0 = st ? t96 - 32 : t96; i0 <= ni; i0 += 192) {
            uint4 x[3];
            uint32_t bad;
            do {
              bad = 0;
#pragma unroll
              for (int q = 0; q < 3; q++) {
                const int i = min(i0 + nt * q, ni) - 224;
                x[q] = ld_relaxed4(&gm[i < 0 ? 672 * st + 896 + i * 4 : i < 28 ? 896 + 112 * c4 + i * 4 : 2240 - 112 + 56 * c8 + i * 4]);
              }
              if (first) { bar_arrive(11, 128); first = false; }
#pragma unroll
              for (int q = 0; q < 3; q++) bad |= mod_bad(x[q], ep << 16);
            } while (__any_sync(~0u, (bad >> 16) != 0) && --bud > 0);
#pragma unroll 1
            for (int q = 0; q < 3; q++) {
              const int i = min(i0 + nt * q, ni) - 224;
              if (i < 0) put_mod4(sb + (st ? OFF_MOD2 : OFF_MOD1), i + 224, x[0], st ? 0x3F003F00u : 0x3F803F80u);
              else { sts32(sb + OFF_GA + i * 8, __byte_perm(x[0].x, x[0].y, 0x5410)); sts32(sb + OFF_GA + i * 8 + 4, __byte_perm(x[0].z, x[0].w, 0x5410)); }
              x[0] = x[1]; x[1] = x[2];
            }
            if (!st) break;
          }
          __syncwarp();
          if (st) { e_arrive(BAR(B_MOD2)); break; }
          __syncwarp();
          bar_arrive(1, 384);
          if (warp > 9) l2_prefetch(a ? (const uint8_t*)P.pwin + b * 12544 : (const uint8_t*)P.pwo + b * 3136, a ? 12544 : 3136, lane);
        }
        const int kv = st;
        if (warp > 9) {
          mbar_wait(BAR(B_KRDY + 2 * kv + a));
          e_bulk_st(g_kv + (size_t)(b1 * 2 + kv) * 16384 + a * 8192, PAGE(12 + 6 * kv + a), 8192);
          e_publish(C_K + 128 * kv + b1);
          continue;
        }
        const uint32_t dst = PAGE(8 + 6 * kv), bar = BAR(B_KALL + kv);
        mbar_wait(BAR(B_XFREE + kv));
        uint32_t todo = rb1 >= 2 ? 3 : rb1;
        while (todo) {
          const uint32_t m = (__ballot_sync(~0u, reached(C_K + 128 * kv + max(b1 - 8 - 8 * (lane & 1), 0), 2 * ep)) | (--bud <= 0 ? 3u : 0u)) & todo;
          if (!m) continue;
          fence_async_glob();
          const int d = (m & 1) ^ 1;
          e_bulk_ld(dst + (1 - d) * 16384, g_kv + (size_t)((b1 - 8 - 8 * d) * 2 + kv) * 16384, 16384, bar);
          todo &= ~(1u << d);
        }
      }
    }
    if (warp == 8) {
      e_expect(BAR(B_MW), 7168);
      e_tma2d(sb + OFF_MW, &P.wmod, 8 * min(b, 111), 0, BAR(B_MW));
      e_tma2d(sb + OFF_MW + 3584, &P.wmod, 8 * min(b, 111), 224, BAR(B_MW));
#pragma unroll
      for (int c = 0; c < 7; c++) { e_expect(BAR(B_X + c), 16384); e_tma2d(PAGE(2 * c), &P.x, 64 * c, 128 * rb1, BAR(B_X + c)); }
      cluster_arrive();
      cluster_wait();
#pragma unroll 1
      for (int p = 0; p < 3; p++) {
        const int col = (56 * j1 & ~15) + (p == 2 ? 0 : 448 + 448 * p);
        e_expect(BAR(B_WK + p), 7 * 8192);
        if (p == 0) bar_sync(11, 128);
        if (p == 1) bar_sync(1, 384);
#pragma unroll 1
        for (int c = (p ^ kh) & 1; c < 7; c += 2) {
          if (c + 7 * p >= 13 && c + 7 * p < 16) { mbar_wait(BAR(B_XFREE)); mbar_wait(BAR(B_XFREE2)); }
          e_tma2d_mc(c + 7 * p == 13 ? PAGE(7) : PAGE((p == 0 ? 14 : p == 1 ? 21 : 0) + c), &P.wqkv, col, 64 * c, BAR(B_WK + p));
        }
      }
#pragma unroll 1
      for (int i = 0; i < 21; i++) {
        if (i == 7) {
          asm volatile(ELECT("cp.async.bulk.prefetch.L2.global [%0], 32768;") ::"l"((const uint8_t*)P.pwsp + (size_t)b * 65536) : "memory");
          asm volatile(ELECT("cp.async.bulk.prefetch.L2.global [%0], 32768;") ::"l"((const uint8_t*)P.pwsp + (size_t)b * 65536 + 32768) : "memory");
        }
        const uint32_t e = c_wprog[i], type = (e >> 25) & 3;
        if (e & 255) mbar_wait(BAR(e & 127), (e >> 7) & 1);
        const uint32_t bar = BAR((e >> 18) & 15);
        const int col = 112 * (type == 1 ? c4 : c8) + 448 * ((e >> 27) & 3), row = 64 * ((e >> 22) & 7);
        const CUtensorMap* m = &P.wqkv + (2 * type - 1);
        if (e >> 29) e_expect(bar, (e >> 29) * 14336);
        e_tma2d(PAGE((e >> 8) & 31), m, col, row, bar);
        e_tma2d(PAGE((e >> 13) & 31), m + 1, col + (type == 1 ? 56 : 64), row, bar);
      }
#pragma unroll 1
      for (int q = 0; q < 4; q++) {
        if (q != 2) mbar_wait(BAR(B_KPASS + q - (q >> 1)), 1);
        const uint32_t bar = BAR(B_B6 + (q > 0)), dst = PAGE(2) + q * 28672;
        if (q < 2) e_expect(bar, q ? 3 * 25088 : 25088);
        e_tma2d(dst, &P.wout64, 112 * cb4, 112 * ((c8 + 2 * q) & 7), bar);
        e_tma2d(dst + 14336, &P.wout48, 112 * cb4 + 64, 112 * ((c8 + 2 * q) & 7), bar);
      }
    } else if (warp == 9) {
#pragma unroll
      for (int c = 0; c < 7; c++) e_expect(BAR(B_A3 + c), 8192);
      mbar_wait(BAR(B_ATT)); mbar_wait(BAR(B_ATT2));
      poll(C_O + h3, 8 * ep);
      rows_mc(g_o + h3 * 28672, 8, B_A3, kh);
      l2_prefetch((const uint8_t*)P.pwout + b * 6272, 6272, lane);
      mbar_wait(BAR(B_Z2PASS));
#pragma unroll 1
      for (int i = 0; i < 16; i++) {
        const int s = i & 3, h = 16 * kh + (i < 8 ? 2 * i : 2 * i - 15);
        if (i == 0 || i == 3) {
          poll(C_Z + 16 * kh + 2 * (lane & 7) + (i & 1), 8 * ep);
          e_bulk_ld(PAGE(26) + (i & 1) * 4096, g_st2 + (2 * kh + (i & 1)) * 512, 4096, BAR(B_RAW + (i & 1)));
        }
        if (i == 1) mbar_wait(BAR(B_STGDONE));
        if (i) mbar_wait(BAR(i >= 4 ? B_S5E + s : B_Z1C + i - 1), i >= 4 ? (i >> 2) - 1 & 1 : 0);
        const uint32_t dst = PAGE(s == 0 ? 20 : 6 * s - 4);
        const uint8_t* src = g_z2t + (size_t)h * FH * 128;
        e_expect(BAR(B_S5F + s), 46080);
        e_tma2d(dst, &P.wsp, 64 * h, 128 * rb, BAR(B_S5F + s));
        e_bulk_ld(dst + 16384, src + 14336 * c8, 14336, BAR(B_S5F + s));
        e_bulk_ld(dst + 30720, src + 14336 * (c8 ^ 1), 14336, BAR(B_S5F + s));
        e_bulk_ld(dst + 45056, g_s.zs + h * 1024, 1024, BAR(B_S5F + s));
      }
    } else {
#pragma unroll
      for (int c = 0; c < 7; c++) e_expect(BAR(B_A4 + 7 * a + c), c ? 8192 : 12288);
      mbar_wait(BAR(B_S3MMA)); mbar_wait(BAR(B_S3MMA2));
      poll(C_X + hh, 4 * ep);
      e_bulk_ld(sb + (a ? OFF_RAW1B : OFF_MW), g_st1 + hh * 512, 4096, BAR(B_A4 + 7 * a));
      rows_mc(g_x1 + hh * 28672, 7 * a, B_A4 + 7 * a, kh ^ a);
      mbar_wait(BAR(B_STG + a));
      e_release(C_Z + hh);
      e_arrive(BAR(B_STGDONE));
      mbar_wait(BAR(B_RAW + a));
#pragma unroll 1
      for (int q = 8 * a; q < 8 * a + 8; q++) {
        const uint4 v = lds128(PAGE(26) + q * 512 + lane * 16);
        const float m0 = __uint_as_float(v.x) * (1.f / 896.f), m1 = __uint_as_float(v.z) * (1.f / 896.f);
        const float r0 = rsqrtf(fmaxf(fmaf(__uint_as_float(v.y), 1.f / 896.f, -m0 * m0), 0.f) + 1e-5f);
        const float r1 = rsqrtf(fmaxf(fmaf(__uint_as_float(v.w), 1.f / 896.f, -m1 * m1), 0.f) + 1e-5f);
        sts32(sb + OFF_R5 + (q * 64 + perm64(2 * lane)) * 2, pack2(r0, r1));
      }
      e_arrive(BAR(B_ST2 + a));
      mbar_wait(BAR(B_QPASS), 1);
      poll(C_U + 2 * rb + kh, 4 * ep);
#pragma unroll 1
      for (int q = 1; q < 4; q++) {
        if (q == 3 && a) mbar_wait(BAR(B_XRD));
        e_expect(BAR(B_A4 + 7 * a + q), 14336);
        e_bulk_ld(PAGE(16) + (3 * a + q - 1) * 14336, g_u + (hh * 8 + ((c8 + 2 * q) & 7)) * 7168, 14336, BAR(B_A4 + 7 * a + q));
      }
    }
    __syncwarp();
    if (warp > 8) cluster_wait();
  } else {
    asm volatile("setmaxnreg.inc.sync.aligned.u32 224;");
    const int a = warp >> 2, w = warp & 3, j = lane & 3, g = lane >> 2;
    const int r0 = 16 * w + g;
    const uint32_t lx = lane & 7, lhi = lane >> 4;
    uint32_t lda[4];
#pragma unroll
    for (int ks = 0; ks < 4; ks++) lda[ks] = sb + (16 * w + (lane & 15)) * 128 + (((2 * ks + lhi) ^ lx) << 4);

    cluster_arrive();
    const uint32_t ldc = sb + lhi * 1024 + (16 * w + (lane & 15)) * 16;
    const int cmo = r0 * 8 + 2 * j;
    if (a == 1) bar_arrive(4, 256);

    uint32_t qf[14];
    {
      uint32_t A[28][4];
      {
        float s2[2][4] = {}, q2[2][4] = {};
        uint32_t pv0 = 0, pv1 = 0;
#pragma unroll
        for (int c = 0; c < 7; c++) {
          mbar_wait(BAR(B_X + c));
#pragma unroll
          for (int ks = 0; ks < 4; ks++) ldsm4(A[4 * c + ks], lda[ks] + a * PG + 2 * c * PG);
#pragma unroll
          for (int ks = 0; ks < 4; ks++) rowsum_mma(s2[ks & 1], A[4 * c + ks]);
          if (c == 0) {
            const float m0 = (s2[0][0] + s2[1][0]) * (1.f / 64.f), m1 = (s2[0][2] + s2[1][2]) * (1.f / 64.f);
            pv0 = pack2(m0, m0); pv1 = pack2(m1, m1);
          }
          if (c == 6) { e_arrive(BAR(B_XFREE)); cluster_wait(); e_arrive_remote(mapa(BAR(B_XFREE2), peer)); }
#pragma unroll
          for (int ks = 0; ks < 4; ks++) {
            uint32_t* x = A[4 * c + ks];
            x[0] = hsub2(x[0], pv0); x[1] = hsub2(x[1], pv1); x[2] = hsub2(x[2], pv0); x[3] = hsub2(x[3], pv1);
            uint32_t sq[4] = {hmul2(x[0], x[0]), hmul2(x[1], x[1]), hmul2(x[2], x[2]), hmul2(x[3], x[3])};
            rowsum_mma(q2[ks & 1], sq);
          }
        }
        const float m0 = fmaf(s2[0][0] + s2[1][0], 1.f / 448.f, -bf_lo(pv0)), m1 = fmaf(s2[0][2] + s2[1][2], 1.f / 448.f, -bf_lo(pv1));
        const float rs0 = rsqrtf(fmaxf(fmaf(q2[0][0] + q2[1][0], 1.f / 448.f, -m0 * m0), 0.f) + 1e-5f);
        const float rs1 = rsqrtf(fmaxf(fmaf(q2[0][2] + q2[1][2], 1.f / 448.f, -m1 * m1), 0.f) + 1e-5f);
        const uint32_t rp0 = pack2(rs0, rs0), rp1 = pack2(rs1, rs1), nm0 = pack2(-m0 * rs0, -m0 * rs0), nm1 = pack2(-m1 * rs1, -m1 * rs1);
#pragma unroll
        for (int i = 0; i < 28; i++) {
          A[i][0] = hfma2(A[i][0], rp0, nm0); A[i][1] = hfma2(A[i][1], rp1, nm1); A[i][2] = hfma2(A[i][2], rp0, nm0); A[i][3] = hfma2(A[i][3], rp1, nm1);
        }
      }
      bar_sync(1, 384);
      if (a == 1) bar_sync(7, 256);
#pragma unroll
      for (int h = 0; h < 14; h++) {
        uint4 cv = lds128(sb + OFF_MOD1 + j * 16 + h * 64), sv = lds128(sb + OFF_MOD1 + 896 + j * 16 + h * 64);
        uint32_t* p = A[2 * h]; uint32_t* q = A[2 * h + 1];
        p[0] = hfma2(p[0], cv.x, sv.x); p[1] = hfma2(p[1], cv.x, sv.x); p[2] = hfma2(p[2], cv.y, sv.y); p[3] = hfma2(p[3], cv.y, sv.y);
        q[0] = hfma2(q[0], cv.z, sv.z); q[1] = hfma2(q[1], cv.z, sv.z); q[2] = hfma2(q[2], cv.w, sv.w); q[3] = hfma2(q[3], cv.w, sv.w);
      }
      if (a == 0) asm volatile("bar.arrive 7, 256;" ::"r"(A[27][3]), "r"(A[20][0]), "r"(A[13][1]) : "memory");
      const uint32_t st_addr = sb + (12 + a) * PG + (16 * w + ((lane >> 3) & 1) * 8 + lx) * 128;
#pragma unroll 1
      for (int p = 0; p < 3; p++) {
        float acc[28];
        const uint32_t wb = (p == 0 ? 14 : p == 1 ? 21 : 0) * (PG / 16) + (j1 & 1), wb6 = p == 1 ? PG / 16 + (j1 & 1) : wb;
        mbar_wait(BAR(B_WK + p));
        bar_sync(4 + a, 256);
        wg_fence();
#pragma unroll
        for (int i = 0; i < 28; i++) wg_rs56<1>(acc, A[i], desc(i < 24 ? wb : wb6, i * 2048, 0), i != 0);
        wg_commit();
        if (p < 2 || a == 0) bar_arrive(5 - a, 256);
        wg_wait<0>(); keep<28>(acc);
        e_arrive(BAR(B_KPASS + p));
#pragma unroll
        for (int i = 0; i < 14; i++) qf[i] = pack2(acc[2 * i], acc[2 * i + 1]);
        if (p < 2) {
          if (p == 1 || rb1 < 2) mbar_wait(BAR(B_XFREE + p));
          if (rb1 < 2) {
#pragma unroll 1
            for (int i = tid; i < (2 - rb1) * 1024; i += 256) sts128(PAGE(8 + 6 * p) + i * 16, make_uint4(0, 0, 0, 0));
          }
          const uint32_t fill = (p == 1 && !(j & 1)) ? 0x3F80u : 0u;
          const uint32_t ta = st_addr + p * 6 * PG;
          stsm4(ta + ((lhi ^ lx) << 4), qf[0], qf[1], qf[2], qf[3]);
          stsm4(ta + (((2 + lhi) ^ lx) << 4), qf[4], qf[5], j < 2 ? qf[6] : fill, j < 2 ? qf[7] : fill);
          stsm4(ta + (((4 + lhi) ^ lx) << 4), j < 2 ? fill : qf[6], j < 2 ? fill : qf[7], qf[8], qf[9]);
          stsm4(ta + (((6 + lhi) ^ lx) << 4), qf[10], qf[11], qf[12], qf[13]);
          fence_async_smem();
          e_arrive(BAR(B_KRDY + 2 * p + a)); e_arrive(BAR(B_KALL + p));
        }
      }
    }
    {
      const int q0 = 128 * rb1 + 64 * a;
      const float sc = 0.18898223650461362f * 1.4426950408889634f;
      const float ninf = __int_as_float(0xff800000);
      uint32_t ow[14];
      const int dd = r0 - 2 * j;
      mbar_wait(BAR(B_KALL));
#pragma unroll 1
      for (int hd = 0; hd < 2; hd++) {
        const uint32_t kb = a * (PG / 16) + hd * 4;
        float sm[96], s0[32], s4[32];
        wg_fence();
#pragma unroll
        for (int ks = 0; ks < 2; ks++) {
          wg_rs64<0>(s0, qf + 4 * ks, desc(kb, 8 * PG + ks * 32, 16), ks);
          wg_rs64<0>(s4, qf + 4 * ks, desc(kb, 12 * PG + ks * 32, 16), ks);
          wg_rs192<0>(sm, qf + 4 * ks, desc(kb, 9 * PG + ks * 32, 16), ks);
        }
        wg_commit();
        wg_wait<0>(); keep<96>(sm); keep<32>(s0); keep<32>(s4);
#pragma unroll
        for (int i = 0; i < 8; i++) qf[i] = qf[i + 6];
        if (q0 < 256) {
#pragma unroll
          for (int i = 0; i < 32; i++) s0[i] = ninf;
        }
#pragma unroll
        for (int i = 0; i < 32; i++) { int t = i >> 2, e = (i >> 1) & 1, f = i & 1; s4[i] = (8 * t + f - 8 * e <= dd) ? s4[i] : s0[i]; }
        float mx[2] = {s4[0], s4[2]};
#pragma unroll
        for (int i = 0; i < 32; i++) mx[(i >> 1) & 1] = fmaxf(mx[(i >> 1) & 1], s4[i]);
#pragma unroll
        for (int k = 0; k < 3; k++) {
          float t[2] = {sm[32 * k], sm[32 * k + 2]};
#pragma unroll
          for (int i = 0; i < 32; i++) t[(i >> 1) & 1] = fmaxf(t[(i >> 1) & 1], sm[32 * k + i]);
          if (q0 - 192 + 64 * k >= 0) { mx[0] = fmaxf(mx[0], t[0]); mx[1] = fmaxf(mx[1], t[1]); }
        }
        mx[0] = -quad_max(mx[0]) * sc; mx[1] = -quad_max(mx[1]) * sc;
        if (hd | a) mbar_wait(BAR(B_TURN - 1 + 2 * hd + a));
        asm volatile("" : "+f"(mx[0]), "+f"(mx[1]) :: "memory");
        uint32_t pm[48], p0[16], p4[16];
#pragma unroll
        for (int k = 0; k < 3; k++) {
          const bool ok = q0 - 192 + 64 * k >= 0;
          const float m0 = ok ? mx[0] : ninf, m1 = ok ? mx[1] : ninf;
#pragma unroll
          for (int i = 16 * k; i < 16 * k + 16; i++) {
            const float m = (i & 1) ? m1 : m0;
            pm[i] = pack2(ex2v(fmaf(sm[2 * i], sc, m)), ex2v(fmaf(sm[2 * i + 1], sc, m)));
          }
        }
#pragma unroll
        for (int i = 0; i < 16; i++) {
          const uint32_t pw = pack2(ex2v(fmaf(s4[2 * i], sc, mx[i & 1])), ex2v(fmaf(s4[2 * i + 1], sc, mx[i & 1])));
          const int lim = 8 * (i >> 1) - 8 * (i & 1);
          const uint32_t mk = (lim + 1 <= dd) ? 0xFFFFFFFFu : (lim <= dd ? 0x0000FFFFu : 0u);
          p4[i] = pw & mk; p0[i] = pw & ~mk;
        }
        if (hd == 0 || a == 0) {
          const uint32_t dep = (pm[3] | pm[9] | pm[15]) | (pm[21] | pm[27] | pm[33]) | (pm[39] | pm[45] | p4[2]) | (p0[7] | p4[12] | p0[15]);
          __syncwarp();
          if (lane == 0) mbar_arrive(BAR(B_TURN + 2 * hd + a) + ((dep >> 31) << 3));
        }
        if (hd == 0) mbar_wait(BAR(B_VALL));
        float o[16];
        wg_fence();
#pragma unroll
        for (int s = 0; s < 12; s++) wg_rs32<1>(o, pm + 4 * s, desc(kb, 15 * PG + s * 2048, 0), s);
#pragma unroll
        for (int s = 0; s < 4; s++) wg_rs32<1>(o, p0 + 4 * s, desc(kb, 14 * PG + s * 2048, 0), 1);
#pragma unroll
        for (int s = 0; s < 4; s++) wg_rs32<1>(o, p4 + 4 * s, desc(kb, 18 * PG + s * 2048, 0), 1);
        wg_commit();
        wg_wait<0>(); keep<16>(o);
        const int src = (lane & 28) | (hd ? 0 : 2);
        const float l0 = rcp(__shfl_sync(~0u, hd ? o[0] : o[12], src)), l1 = rcp(__shfl_sync(~0u, hd ? o[2] : o[14], src));
        const bool keep3 = hd == 1 && j < 2;
        const uint32_t e0 = ow[12], e1 = ow[13];
#pragma unroll
        for (int i = 0; i < 6; i++) ow[i] = ow[i + 6];
#pragma unroll
        for (int t = 0; t < 4; t++) { ow[6 + 2 * t] = pack2(o[4 * t] * l0, o[4 * t + 1] * l0); ow[7 + 2 * t] = pack2(o[4 * t + 2] * l1, o[4 * t + 3] * l1); }
        ow[6] = keep3 ? e0 : ow[6]; ow[7] = keep3 ? e1 : ow[7];
      }
      store_cm<7>(ow, g_o + ((2 * rb1 + a) * 56 + 7 * j1) * 512 + cmo);
      if (w == 0 && lane < 4) stg128(g_st2 + st2pos(2 * rb1 + a) + 8 * j1 + 2 * lane, make_uint4(0, 0, 0, 0));
      e_arrive(BAR(B_ATT)); e_arrive_remote(mapa(BAR(B_ATT2), peer));
      bar_sync(2 + a, 128);
      if (w == 0) e_release(C_O + 2 * rb1 + a);
    }
    {
      uint32_t xr[16];
      {
        const int rr = (lane * 37) >> 8, cc = lane - 7 * rr;
        const uint32_t stg = PAGE(26) + warp * 1024;
        uint4 v[4];
        if (lane < 28) {
#pragma unroll
          for (int k = 0; k < 4; k++) v[k] = __ldg((const uint4*)(P.px + (size_t)(64 * h3 + 16 * w + 4 * k + rr) * DM + 112 * c4 + 56 * a) + cc);
        }
#pragma unroll
        for (int hf = 0; hf < 2; hf++) {
          if (lane < 28) { sts128(stg + lane * 16, v[2 * hf]); sts128(stg + 448 + lane * 16, v[2 * hf + 1]); }
          __syncwarp();
          uint32_t m[8];
          ldsm4(m, stg + lx * 112 + (lane >> 3) * 16);
          ldsm4(m + 4, stg + lx * 112 + min(4 + (lane >> 3), 6) * 16);
#pragma unroll
          for (int t = 0; t < 7; t++) xr[2 * t + hf] = m[t];
          __syncwarp();
        }
      }
      e_arrive(BAR(B_XST));
      float acc[28];
      mbar_wait(BAR(B_WO));
#pragma unroll 1
      for (int c = 0; c < 7; c++) {
        mbar_wait(BAR(B_A3 + c), 1);
        wg_fence();
#pragma unroll
        for (int ks = 0; ks < 4; ks++) wg_ss56<1>(acc, (uint64_t)(c * (PG / 16) + ((SMEM0 + 8 * PG + ks * 2048) >> 4) + (64u << 16)) | (uint64_t)8 << 32, desc(((c < 4 ? 2 * c : 2 * c + 12) + a) * (PG / 16), ks * 2048, 0), (c | ks) != 0);
      }
      wg_commit();
      mbar_wait(BAR(B_MOD2));
      wg_wait<0>(); keep<28>(acc);
      e_arrive(BAR(B_S3MMA)); e_arrive_remote(mapa(BAR(B_S3MMA2), peer));
#pragma unroll
      for (int t = 0; t < 7; t++) {
        const uint32_t ga = lds32(sb + OFF_GA + a * 112 + j * 4 + t * 16);
        xr[2 * t] = hfma2(ga, pack2(acc[4 * t], acc[4 * t + 1]), xr[2 * t]);
        xr[2 * t + 1] = hfma2(ga, pack2(acc[4 * t + 2], acc[4 * t + 3]), xr[2 * t + 1]);
      }
      store_cm<7>(xr, g_x1 + (h3 * 56 + 14 * c4 + 7 * a) * 512 + cmo);
      const uint32_t p0 = __byte_perm(__shfl_sync(~0u, xr[0], lane & 28), 0, 0x1010), p1 = __byte_perm(__shfl_sync(~0u, xr[1], lane & 28), 0, 0x1010);
      xr[14] = p0; xr[15] = p1;
      float s[4] = {}, q[4] = {};
#pragma unroll
      for (int i = 0; i < 4; i++) {
        uint32_t d[4], e[4];
#pragma unroll
        for (int k = 0; k < 4; k++) { d[k] = hsub2(xr[4 * i + k], (k & 1) ? p1 : p0); e[k] = hmul2(d[k], d[k]); }
        rowsum_mma(s, d);
        rowsum_mma(q, e);
      }
      if (j < 2) {
        const float sd = j ? s[2] : s[0];
        g_st1[(h3 * 8 + 2 * c4 + a) * 64 + r0 + 8 * j] = make_float2(fmaf(bf_lo(j ? p1 : p0), 56.f, sd), fmaf(-sd * (1.f / 56.f), sd, j ? q[2] : q[0]));
      }
      bar_sync(1, 256);
      if (warp == 0) e_release(C_X + h3);
    }
    uint32_t zp[28];
    {
      uint32_t A[28][4];
      mbar_wait(BAR(B_MOD2));
      uint32_t rh[2], rl[2], mr[2];
      mbar_wait(BAR(B_A4 + 7 * a));
#pragma unroll
      for (int e = 0; e < 2; e++) {
        float2 q[8];
        float mean = 0.f, m2 = 0.f;
#pragma unroll
        for (int i = 0; i < 8; i++) { q[i] = lds64f(sb + (a ? OFF_RAW1B : OFF_MW) + (r0 + 8 * e) * 8 + i * 512); mean += q[i].x; m2 += q[i].y; }
        mean *= 1.f / 448.f;
#pragma unroll
        for (int i = 0; i < 8; i++) { const float d = fmaf(q[i].x, 1.f / 56.f, -mean); m2 = fmaf(56.f * d, d, m2); }
        const float rstd = rsqrtf(fmaxf(m2, 0.f) * (1.f / 448.f) + 1e-5f);
        rh[e] = pack2(rstd, rstd);
        const float lo = rstd - bf_lo(rh[e]), nm = -mean * rstd;
        rl[e] = pack2(lo, lo); mr[e] = pack2(nm, nm);
      }
      if (a == 1) bar_arrive(4, 256);
#pragma unroll
      for (int c = 0; c < 7; c++) {
        if (c) mbar_wait(BAR(B_A4 + 7 * a + c));
#pragma unroll
        for (int ks = 0; ks < 4; ks++) ldsm4(A[4 * c + ks], ldc + 7 * a * PG + c * PG + ks * 2048);
        if (c == 6) e_arrive(BAR(B_A4RD + a));
        if (c == 1 && a == 0) e_arrive(BAR(B_A4E));
#pragma unroll
        for (int h = 0; h < 2; h++) {
          uint4 cv = lds128(sb + OFF_MOD2 + j * 16 + (2 * c + h) * 64), sv = lds128(sb + OFF_MOD2 + 896 + j * 16 + (2 * c + h) * 64);
          uint32_t cw[4] = {cv.x, cv.y, cv.z, cv.w}, sw[4] = {sv.x, sv.y, sv.z, sv.w};
#pragma unroll
          for (int i = 0; i < 8; i++) {
            uint32_t& x = A[4 * c + 2 * h + (i >> 2)][i & 3];
            x = hfma2(hfma2(x, rh[i & 1], hfma2(x, rl[i & 1], mr[i & 1])), cw[i >> 1], sw[i >> 1]);
          }
        }
      }
#pragma unroll 1
      for (int p = 0; p < 2; p++) {
        float acc[56];
        mbar_wait(BAR(B_Z2W + 3 * p));
        bar_sync(4 + a, 256);
#pragma unroll
        for (int c = 0; c < 7; c++) {
          if (c == 2 || c == 4) { if (p) mbar_wait(BAR(B_Z1W + c / 2)); }
          if (c == 3 || c == 6) { if (!p) mbar_wait(BAR(B_Z2W + c / 3)); }
          wg_fence();
          const int q2 = c < 2 ? 16 + 2 * c : c == 2 ? 15 : c < 6 ? 14 + 2 * c : 0, l2 = c == 2 ? 11 : 1;
          const int q1 = c == 0 ? 4 : c == 1 ? 6 : c == 2 ? 9 : c == 3 ? 11 : c == 4 ? 16 : c == 5 ? 18 : 0, l1 = c == 1 ? 8 : 1;
          const uint32_t d16 = p ? (q1 * (PG / 16)) | (l1 * (PG / 16)) << 16 : (q2 * (PG / 16)) | (l2 * (PG / 16)) << 16;
#pragma unroll
          for (int ks = 0; ks < 4; ks++) wg_rs112<1>(acc, A[4 * c + ks], desc(d16, ks * 2048, 0), (c | ks) != 0);
          wg_commit();
          if (c == 3) { wg_wait<2>(); e_arrive(BAR(B_Z2C + p)); }
          if (c == 5) { wg_wait<2>(); if (p) e_arrive(BAR(B_Z1C + 1)); }
        }
        if (p == 0 || a == 0) bar_arrive(5 - a, 256);
        wg_wait<1>();
        if (p) e_arrive(BAR(B_Z1C + 2));
        wg_wait<0>(); keep<56>(acc);
        if (!p) e_arrive(BAR(B_Z2PASS));
        float s2[2] = {0.f, 0.f}, q2[2] = {0.f, 0.f};
#pragma unroll
        for (int i = 0; i < 28; i++) {
          const float x = gelu_h(acc[2 * i]), y = gelu_h(acc[2 * i + 1]);
          zp[i] = pack2(x, y);
          s2[i & 1] += x + y;
          q2[i & 1] = fmaf(x, x, fmaf(y, y, q2[i & 1]));
        }
        if (p == 0) {
          const uint32_t sp = PAGE(a ? 7 : 2), stg = sp + (lhi * 8 + lx) * 128 + (((2 * w + ((lane >> 3) & 1)) ^ lx) << 4);
#pragma unroll
          for (int t = 0; t < 7; t++) stsm4t(stg + t * 2048, zp[4 * t], zp[4 * t + 1], zp[4 * t + 2], zp[4 * t + 3]);
          float sv = (j & 1) ? s2[1] : s2[0], qv = (j & 1) ? q2[1] : q2[0];
          sv += __shfl_xor_sync(~0u, (j & 1) ? s2[0] : s2[1], 1); qv += __shfl_xor_sync(~0u, (j & 1) ? q2[0] : q2[1], 1);
          sv += __shfl_xor_sync(~0u, sv, 2); qv += __shfl_xor_sync(~0u, qv, 2);
          if (j < 2) {
            asm volatile("red.relaxed.gpu.global.add.v2.f32 [%0], {%1, %2};" ::"l"(g_st2 + st2pos(2 * rb + a) + r0 + 8 * j), "f"(sv), "f"(qv) : "memory");
            *(uint16_t*)(g_s.zs + (2 * rb + a) * 1024 + c8 * 128 + (((2 * w + j) ^ c8) << 4) + g * 2) = (uint16_t)pack2(sv * (1.f / 896.f), 0.f);
          }
          bar_sync(2 + a, 128);
          uint8_t* zg = g_z2t + ((size_t)(2 * rb + a) * FH + 112 * c8) * 128 + (tid & 127) * 16;
#pragma unroll
          for (int t = 0; t < 7; t++) stg128(zg + t * 2048, lds128(sp + (tid & 127) * 16 + t * 2048));
          e_arrive(BAR(B_STG + a));
        }
      }
    }
    {
      float acc[116];
      uint32_t A[2][16];
      const size_t row = 128 * rb + 64 * a + r0;
      uint16_t bs0, bs1;
      asm volatile("ld.global.nc.u16 %0, [%2];\nld.global.nc.u16 %1, [%2+16];" : "=h"(bs0), "=h"(bs1) : "l"(P.pbsp + row));
      auto prep = [&](int i, uint32_t* Af) {
        if ((i & 7) == 0) {
          mbar_wait(BAR(B_ST2 + (i >> 3)));
          if (i) {
            e_arrive_remote(mapa(BAR(B_X5FREE), peer));
          }
        }
        const int s = i & 3;
        mbar_wait(BAR(B_S5F + s), (i >> 2) & 1);
        const uint32_t pa = PG * (s == 0 ? 20 : 6 * s - 4) + a * PG;
#pragma unroll
        for (int ks = 0; ks < 4; ks++) ldsm4(Af + 4 * ks, lda[ks] + pa);
#pragma unroll
        for (int h = 0; h < 2; h++) {
          uint4 rv = lds128(sb + OFF_R5 + i * 128 + j * 32 + h * 16);
          uint32_t* p = Af + 8 * h;
          p[0] = hmul2(p[0], rv.x); p[1] = hmul2(p[1], rv.x); p[2] = hmul2(p[2], rv.y); p[3] = hmul2(p[3], rv.y);
          p[4] = hmul2(p[4], rv.z); p[5] = hmul2(p[5], rv.z); p[6] = hmul2(p[6], rv.w); p[7] = hmul2(p[7], rv.w);
        }
      };
      auto mma = [&](int i, const uint32_t* Af) {
        const int s = i & 3;
        wg_fence();
#pragma unroll
        for (int ks = 0; ks < 4; ks++) wg_rs232<0>(acc, Af + 4 * ks, desc((s == 0 ? 22 : 6 * s - 2) * (PG / 16), ks * 32, 16), (i | ks) != 0);
        wg_commit();
        wg_wait<1>();
        if (i > 0) e_arrive(BAR(i < 14 ? B_S5E + ((i - 1) & 3) : B_KPASS - 14 + i));
      };
#pragma unroll 1
      for (int i = 0; i < 16; i += 2) {
        if (i > 0) mma(i - 1, A[1]);
        prep(i, A[0]);
        mma(i, A[0]);
        prep(i + 1, A[1]);
      }
      mma(15, A[1]);
      mbar_wait(BAR(B_X5FREE));
      wg_wait<0>(); keep<116>(acc);
      float c0 = quad_sum(acc[112] + acc[113]), c1 = quad_sum(acc[114] + acc[115]);
      e_arrive(BAR(B_QPASS));
      const uint32_t xw = (a ? OFF_XB5_1 : OFF_XB5_0) + w * 3584, xoff = xw + lane * 16;
      const uint32_t rx = mapa(sb + xoff, peer), rbar = mapa(BAR(B_XB5 + a), peer);
#pragma unroll
      for (int q = 0; q < 7; q++) {
        const float* s = acc + 56 + 8 * q;
        st_async4(rx + q * 512, pack2(s[0] - c0, s[1] - c0), pack2(s[2] - c1, s[3] - c1), pack2(s[4] - c0, s[5] - c0), pack2(s[6] - c1, s[7] - c1), rbar);
      }
      c0 = bf_lo(bs0) - c0; c1 = bf_lo(bs1) - c1;
      mbar_wait(BAR(B_XB5 + a));
#pragma unroll
      for (int q = 0; q < 7; q++) {
        const uint4 v = lds128(sb + xoff + q * 512);
        const uint32_t vw[4] = {v.x, v.y, v.z, v.w};
#pragma unroll
        for (int e = 0; e < 4; e++) {
          const int i = 4 * q + e;
          const float cc = (e & 1) ? c1 : c0;
          zp[i] = hmul2(pack2(acc[2 * i] + cc + bf_lo(vw[e]), acc[2 * i + 1] + cc + bf_hi(vw[e])), zp[i]);
        }
      }
      store_cm<14>(zp, g_u + ((2 * rb + a) * 112 + 14 * c8) * 512 + cmo);
      __syncwarp();
      e_arrive_remote(mapa(BAR(B_X6FREE), peer));
      if (a == 1) e_arrive(BAR(B_XRD));
      bar_sync(1, 256);
      if (warp == 0) e_release(C_U + rb * 2 + kh);
    }
    {
      uint32_t xr[14];
#pragma unroll
      for (int t = 0; t < 14; t++) xr[t] = __ldcg((const uint32_t*)(g_x1 + ((2 * rb + a) * 56 + 7 * c8 + (t >> 1)) * 512 + (t & 1) * 64 + cmo));
      float acc[56];
      uint32_t A[2][28];
      auto mma6 = [&](int q, const uint32_t* Af) {
        wg_fence();
#pragma unroll
        for (int ks = 0; ks < 7; ks++) wg_rs112<1>(acc, Af + 4 * ks, desc(0, 2 * PG + q * 28672 + ks * 2048, 14336), (q | ks) != 0);
        wg_commit();
      };
      mbar_wait(BAR(B_B6));
      mma6(0, zp);
      mbar_wait(BAR(B_B6 + 1));
#pragma unroll
      for (int q = 1; q < 4; q++) {
        mbar_wait(BAR(B_A4 + 7 * a + q), 1);
        if (q == 3) wg_wait<1>();
#pragma unroll
        for (int ks = 0; ks < 7; ks++) ldsm4(A[q & 1] + 4 * ks, ldc + 16 * PG + (3 * a + q - 1) * 14336 + ks * 2048);
        mma6(q, A[q & 1]);
      }
      mbar_wait(BAR(B_X6FREE));
      wg_wait<0>(); keep<56>(acc);
      uint32_t ps[14];
#pragma unroll
      for (int i = 0; i < 14; i++) {
        ps[i] = pack2(kh ? acc[2 * i] : acc[28 + 2 * i], kh ? acc[2 * i + 1] : acc[29 + 2 * i]);
        acc[2 * i] = kh ? acc[28 + 2 * i] : acc[2 * i]; acc[2 * i + 1] = kh ? acc[29 + 2 * i] : acc[2 * i + 1];
      }
      const uint32_t xw = a * PG + w * 2048, xoff = xw + lane * 16;
      const uint32_t rx = mapa(sb + xoff, peer), rbar = mapa(BAR(B_XB6 + a), peer);
#pragma unroll
      for (int q = 0; q < 3; q++) st_async4(rx + q * 512, ps[4 * q], ps[4 * q + 1], ps[4 * q + 2], ps[4 * q + 3], rbar);
      st_async2(rx + 1536 - lane * 8, ps[12], ps[13], rbar);
      mbar_wait(BAR(B_XB6 + a));
#pragma unroll
      for (int q = 0; q < 3; q++) { uint4 v = lds128(sb + xoff + q * 512); ps[4 * q] = v.x; ps[4 * q + 1] = v.y; ps[4 * q + 2] = v.z; ps[4 * q + 3] = v.w; }
      { float2 v = lds64f(sb + xw + 1536 + lane * 8); ps[12] = __float_as_uint(v.x); ps[13] = __float_as_uint(v.y); }
#pragma unroll
      for (int t = 0; t < 7; t++) {
        const uint32_t gb = lds32(sb + OFF_GB + j * 4 + t * 16);
#pragma unroll
        for (int e = 0; e < 2; e++) {
          const int i = 2 * t + e;
          xr[i] = pack2(fmaf(bf_lo(gb), acc[2 * i] + bf_lo(ps[i]), bf_lo(xr[i])), fmaf(bf_hi(gb), acc[2 * i + 1] + bf_hi(ps[i]), bf_hi(xr[i])));
        }
      }
      __syncwarp();
      store_rows<7>(xr, sb + xw, P.out + (size_t)(128 * rb + 64 * a + 16 * w) * DM + 56 * c8, DM, lane);
    }
    if (b == 0 && tid == 0) st_relaxed(&g_epoch, ld_relaxed(&g_epoch) + 1);
  }
}

typedef CUresult (*EncodeFn)(CUtensorMap*, CUtensorMapDataType, cuuint32_t, void*, const cuuint64_t*, const cuuint64_t*, const cuuint32_t*,
                             const cuuint32_t*, CUtensorMapInterleave, CUtensorMapSwizzle, CUtensorMapL2promotion, CUtensorMapFloatOOBfill);

void make_map(EncodeFn enc, CUtensorMap* m, const void* ptr, uint64_t inner, uint64_t outer, uint32_t bi, uint32_t bo,
              CUtensorMapSwizzle sw = CU_TENSOR_MAP_SWIZZLE_128B) {
  cuuint64_t dims[2] = {inner, outer}, strides[1] = {inner * 2};
  cuuint32_t box[2] = {bi, bo}, es[2] = {1, 1};
  enc(m, CU_TENSOR_MAP_DATA_TYPE_BFLOAT16, 2, const_cast<void*>(ptr), dims, strides, box, es, CU_TENSOR_MAP_INTERLEAVE_NONE,
      sw, CU_TENSOR_MAP_L2_PROMOTION_L2_256B, CU_TENSOR_MAP_FLOAT_OOB_FILL_NONE);
}

}

extern "C" void kernel_launch(void* const* d_in, const int* in_sizes, int n_in, void* d_out, int out_size) {
  static EncodeFn enc = nullptr;
  if (!enc) {
    void* fn = nullptr;
    cudaDriverEntryPointQueryResult st;
    cudaGetDriverEntryPoint("cuTensorMapEncodeTiled", &fn, cudaEnableDefault, &st);
    enc = (EncodeFn)fn;
    cudaFuncSetAttribute(fused_kernel, cudaFuncAttributeMaxDynamicSharedMemorySize, SMEM_BYTES);
  }
  typedef const __nv_bfloat16* bp;
  Params P;
  P.px = (bp)d_in[0]; P.pwqkv = (bp)d_in[1]; P.pwo = (bp)d_in[2]; P.pwin = (bp)d_in[4]; P.pwsp = (bp)d_in[5]; P.pbsp = (bp)d_in[6];
  P.pwout = (bp)d_in[7]; P.pc = (bp)d_in[8]; P.pwmod = (bp)d_in[9]; P.out = (__nv_bfloat16*)d_out;
  make_map(enc, &P.wmod, d_in[9], 6 * DM, DM, 8, 224, CU_TENSOR_MAP_SWIZZLE_NONE);
  make_map(enc, &P.wmods, d_in[9], 6 * DM, DM, 224, 224, CU_TENSOR_MAP_SWIZZLE_NONE);
  make_map(enc, &P.x, d_in[0], DM, SEQ, 64, 128);
  make_map(enc, &P.wqkv, d_in[1], 3 * DM, DM, 64, 64);
  make_map(enc, &P.wo64, d_in[2], DM, DM, 56, 64);
  make_map(enc, &P.wo48, d_in[2], DM, DM, 56, 64);
  make_map(enc, &P.win64, d_in[4], 2 * FH, DM, 64, 64);
  make_map(enc, &P.win48, d_in[4], 2 * FH, DM, 48, 64);
  make_map(enc, &P.wsp, d_in[5], SEQ, SEQ, 64, 128);
  make_map(enc, &P.wout64, d_in[7], DM, FH, 64, 112);
  make_map(enc, &P.wout48, d_in[7], DM, FH, 48, 112);
  fused_kernel<<<132, 384, SMEM_BYTES, cudaStreamPerThread>>>(P);
}
```

```cpp
#include <cuda_runtime.h>
#include <cuda_bf16.h>
#include <cuda.h>
#include <stdint.h>

namespace {

constexpr int SEQ = 2048, DM = 448, FH = 896;
constexpr uint32_t PG = 8192;
constexpr uint32_t MISC = 27 * PG;
constexpr uint32_t OFF_MW = MISC;
constexpr uint32_t OFF_MOD1 = MISC + 3072;
constexpr uint32_t OFF_MOD2 = OFF_MOD1 + 2048;
constexpr uint32_t OFF_GA = OFF_MOD2 + 1792;
constexpr uint32_t OFF_GB = OFF_GA + 224;
constexpr uint32_t OFF_R5 = OFF_GB + 112;
constexpr uint32_t OFF_RED = OFF_R5 + 2048;
constexpr uint32_t OFF_BAR = OFF_RED + 256;
constexpr uint32_t SMEM_BYTES = OFF_BAR + 896;
constexpr uint32_t OFF_RAW1B = 14 * PG;
constexpr uint32_t OFF_XB5_0 = 0;
constexpr uint32_t OFF_XB5_1 = 25 * PG + 5120;
static_assert(SMEM_BYTES <= 232448, "smem");

enum : int {
  B_WK = 0, B_WV, B_WQ, B_WO, B_Z2W  , B_Z1W = B_Z2W + 3  , B_B6 = B_Z1W + 3  , B_ST2 = B_B6 + 3  ,
  B_XB5 = B_ST2 + 2  , B_XB6 = B_XB5 + 2  , B_RAW = B_XB6 + 2  , B_X = B_RAW + 2  , B_A3 = B_X, B_A4 = B_A3 + 7  , B_MW = B_A4 + 14, B_S5F  , B_END1 = B_S5F + 4,
  B_CNT2 = 48, B_STGDONE = B_CNT2, B_MOD2,
  B_CNT4 = 60, B_A4RD = B_CNT4  , B_KRDY = B_A4RD + 2  ,
  B_A4E = B_KRDY + 4, B_XRD, B_TURN  , B_END4 = B_TURN + 3,
  B_CNT8 = 84, B_XFREE = B_CNT8, B_KPASS, B_VPASS, B_QPASS, B_ATT, B_Z2PASS, B_Z2C, B_Z1C  , B_S5E = B_Z1C + 3  ,
  B_X5FREE = B_S5E + 4, B_X6FREE, B_KALL, B_VALL, B_XFREE2, B_ATT2, B_S3MMA, B_S3MMA2, B_END8,
  B_COUNT = 108,
  PH1 = 128
};
static_assert(B_XB5 >= 12 && B_RAW + 2 <= 24 && B_X5FREE >= 96 && B_END1 <= B_CNT2 && B_END4 <= B_CNT8 && B_END8 <= B_COUNT, "barriers");

constexpr int C_K = 0  , C_O = 256, C_X = 288, C_Z = 320, C_U = 352, C_COUNT = 416;

constexpr int CSTR = 64;
constexpr int MODREP = 16;
struct Small {
  uint32_t epoch, pad[31];
  uint32_t mod[MODREP * 2688];
  uint32_t cnt[C_COUNT * CSTR];
  float2 st2[SEQ];
  uint8_t zs[32 * 1024];
  float2 st1[SEQ * 8];
};
__device__ __align__(1024) Small g_s;
#define g_epoch g_s.epoch
#define g_mod g_s.mod
#define g_cnt g_s.cnt
#define g_st1 g_s.st1
#define g_st2 g_s.st2
__device__ __align__(1024) uint8_t g_kv[16 * 8 * 2 * 16384];
__device__ __align__(1024) __nv_bfloat16 g_o[SEQ * DM];
__device__ __align__(1024) __nv_bfloat16 g_x1[SEQ * DM];
__device__ __align__(1024) __nv_bfloat16 g_u[SEQ * FH];
__device__ __align__(1024) uint8_t g_z2t[32 * FH * 128];

struct Params {
  CUtensorMap wmods, wmod, x, wsp, wqkv, wo64, wo48, win64, win48, wout64, wout48;
  const __nv_bfloat16 *px, *pwqkv, *pwo, *pwin, *pwsp, *pbsp, *pwout, *pc, *pwmod;
  __nv_bfloat16* out;
};

__device__ __forceinline__ uint32_t smem_u32(const void* p) { return (uint32_t)__cvta_generic_to_shared(p); }
__device__ __forceinline__ void mbar_init(uint32_t bar, uint32_t cnt) { asm volatile("mbarrier.init.shared::cta.b64 [%0], %1;" ::"r"(bar), "r"(cnt)); }
__device__ __forceinline__ void mbar_arrive(uint32_t bar) { asm volatile("mbarrier.arrive.shared::cta.b64 _, [%0];" ::"r"(bar) : "memory"); }
__device__ __forceinline__ uint32_t mapa(uint32_t addr, uint32_t cta) { uint32_t r; asm volatile("mapa.shared::cluster.u32 %0, %1, %2;" : "=r"(r) : "r"(addr), "r"(cta)); return r; }
__device__ __forceinline__ void mbar_wait2(uint32_t bar, uint32_t par, int& bud) {
  asm volatile("{\n.reg .pred p;\nWLOOP:\nmbarrier.try_wait.parity.shared::cta.b64 p, [%1], %2;\n@p bra WDONE;\n"
               "add.s32 %0, %0, -1;\nsetp.gt.s32 p, %0, 0;\n@p bra WLOOP;\nWDONE:\n}" : "+r"(bud) : "r"(bar), "r"(par) : "memory");
}
__device__ __forceinline__ void bar_sync(int id, int n) { asm volatile("bar.sync %0, %1;" ::"r"(id), "r"(n) : "memory"); }
__device__ __forceinline__ void bar_arrive(int id, int n) { asm volatile("bar.arrive %0, %1;" ::"r"(id), "r"(n) : "memory"); }
__device__ __forceinline__ void fence_async_smem() { asm volatile("fence.proxy.async.shared::cta;" ::: "memory"); }
__device__ __forceinline__ void fence_async_glob() { asm volatile("fence.proxy.async.global;" ::: "memory"); }
#define ELECT(body) "{\n.reg .pred p;\nelect.sync _|p, 0xffffffff;\n@p " body "\n}"
__device__ __forceinline__ void e_expect(uint32_t bar, uint32_t bytes) { asm volatile(ELECT("mbarrier.arrive.expect_tx.shared::cta.b64 _, [%0], %1;") ::"r"(bar), "r"(bytes) : "memory"); }
__device__ __forceinline__ void e_arrive(uint32_t bar) { __syncwarp(); asm volatile(ELECT("mbarrier.arrive.shared::cta.b64 _, [%0];") ::"r"(bar) : "memory"); }
__device__ __forceinline__ void e_arrive_dep(uint32_t bar, uint32_t dep) {
  __syncwarp();
  asm volatile("{\n.reg .pred p, q;\nelect.sync _|p, 0xffffffff;\nsetp.ge.and.s32 q, %1, 0, p;\n@q mbarrier.arrive.shared::cluster.b64 _, [%0];\n}" ::"r"(bar), "r"(dep) : "memory");
}
__device__ __forceinline__ void e_arrive_remote(uint32_t rbar) { asm volatile(ELECT("mbarrier.arrive.shared::cluster.b64 _, [%0];") ::"r"(rbar) : "memory"); }
__device__ __forceinline__ void e_tma2d(uint32_t dst, const CUtensorMap* map, int c0, int c1, uint32_t bar) {
  asm volatile(ELECT("cp.async.bulk.tensor.2d.shared::cluster.global.mbarrier::complete_tx::bytes [%0], [%1, {%3, %4}], [%2];")
               ::"r"(dst), "l"(map), "r"(bar), "r"(c0), "r"(c1) : "memory");
}
__device__ __forceinline__ void e_tma2d_mc(uint32_t dst, const CUtensorMap* map, int c0, int c1, uint32_t bar) {
  asm volatile(ELECT("cp.async.bulk.tensor.2d.shared::cluster.global.mbarrier::complete_tx::bytes.multicast::cluster [%0], [%1, {%3, %4}], [%2], %5;")
               ::"r"(dst), "l"(map), "r"(bar), "r"(c0), "r"(c1), "h"((uint16_t)3) : "memory");
}
__device__ __forceinline__ void e_bulk_ld(uint32_t dst, const void* src, uint32_t bytes, uint32_t bar) {
  asm volatile(ELECT("cp.async.bulk.shared::cluster.global.mbarrier::complete_tx::bytes [%0], [%1], %2, [%3];")
               ::"r"(dst), "l"(src), "r"(bytes), "r"(bar) : "memory");
}
__device__ __forceinline__ void e_bulk_ld_mc(uint32_t dst, const void* src, uint32_t bytes, uint32_t bar) {
  asm volatile(ELECT("cp.async.bulk.shared::cluster.global.mbarrier::complete_tx::bytes.multicast::cluster [%0], [%1], %2, [%3], %4;")
               ::"r"(dst), "l"(src), "r"(bytes), "r"(bar), "h"((uint16_t)3) : "memory");
}
__device__ __forceinline__ void e_bulk_st(void* dst, uint32_t src, uint32_t bytes) {
  asm volatile(ELECT("cp.async.bulk.global.shared::cta.bulk_group [%0], [%1], %2;") ::"l"(dst), "r"(src), "r"(bytes) : "memory");
}
__device__ __forceinline__ void bulk_done() {
  asm volatile("cp.async.bulk.commit_group;" ::: "memory");
  asm volatile("cp.async.bulk.wait_group 0;" ::: "memory");
  __syncwarp();
}
__device__ __forceinline__ void l2_prefetch(const void* p, int bytes, int lane) {
#pragma unroll 1
  for (int o = lane * 128; o < bytes; o += 4096) asm volatile("prefetch.global.L2 [%0];" ::"l"((const uint8_t*)p + o) : "memory");
}
__device__ __forceinline__ void prefetch_map(const CUtensorMap* m) { asm volatile("prefetch.tensormap [%0];" ::"l"(m) : "memory"); }
__device__ __forceinline__ uint32_t ld_acquire(const uint32_t* p) { uint32_t v; asm volatile("ld.acquire.gpu.global.u32 %0, [%1];" : "=r"(v) : "l"(p) : "memory"); return v; }
__device__ __forceinline__ uint32_t ld_relaxed(const uint32_t* p) { uint32_t v; asm volatile("ld.relaxed.gpu.global.u32 %0, [%1];" : "=r"(v) : "l"(p) : "memory"); return v; }
__device__ __forceinline__ uint4 ld_relaxed4(const uint32_t* p) {
  uint4 v; asm volatile("ld.relaxed.gpu.global.v4.u32 {%0,%1,%2,%3}, [%4];" : "=r"(v.x), "=r"(v.y), "=r"(v.z), "=r"(v.w) : "l"(p) : "memory"); return v;
}
__device__ __forceinline__ void st_relaxed(uint32_t* p, uint32_t v) { asm volatile("st.relaxed.gpu.global.u32 [%0], %1;" ::"l"(p), "r"(v) : "memory"); }
__device__ __forceinline__ void e_release(int c) { __syncwarp(); asm volatile(ELECT("red.release.gpu.global.add.u32 [%0], 1;") ::"l"(&g_cnt[c * CSTR]) : "memory"); }
__device__ __forceinline__ void e_publish(int c) { bulk_done(); fence_async_glob(); e_release(c); }
__device__ __forceinline__ bool reached(int c, uint32_t target) { return (int)(ld_acquire(&g_cnt[c * CSTR]) - target) >= 0; }
__device__ __forceinline__ void ldsm4(uint32_t* r, uint32_t addr) {
  asm volatile("ldmatrix.sync.aligned.m8n8.x4.shared.b16 {%0,%1,%2,%3}, [%4];" : "=r"(r[0]), "=r"(r[1]), "=r"(r[2]), "=r"(r[3]) : "r"(addr) : "memory");
}
__device__ __forceinline__ void stsm4(uint32_t addr, uint32_t r0, uint32_t r1, uint32_t r2, uint32_t r3) {
  asm volatile("stmatrix.sync.aligned.m8n8.x4.shared.b16 [%0], {%1,%2,%3,%4};" ::"r"(addr), "r"(r0), "r"(r1), "r"(r2), "r"(r3) : "memory");
}
__device__ __forceinline__ void stsm2(uint32_t addr, uint32_t r0, uint32_t r1) {
  asm volatile("stmatrix.sync.aligned.m8n8.x2.shared.b16 [%0], {%1,%2};" ::"r"(addr), "r"(r0), "r"(r1) : "memory");
}
__device__ __forceinline__ void stsm4t(uint32_t addr, uint32_t r0, uint32_t r1, uint32_t r2, uint32_t r3) {
  asm volatile("stmatrix.sync.aligned.m8n8.x4.trans.shared.b16 [%0], {%1,%2,%3,%4};" ::"r"(addr), "r"(r0), "r"(r1), "r"(r2), "r"(r3) : "memory");
}
__device__ __forceinline__ uint4 lds128(uint32_t addr) {
  uint4 v; asm volatile("ld.shared.v4.u32 {%0,%1,%2,%3}, [%4];" : "=r"(v.x), "=r"(v.y), "=r"(v.z), "=r"(v.w) : "r"(addr) : "memory"); return v;
}
__device__ __forceinline__ float2 lds64f(uint32_t addr) {
  float2 v; asm volatile("ld.shared.v2.f32 {%0,%1}, [%2];" : "=f"(v.x), "=f"(v.y) : "r"(addr) : "memory"); return v;
}
__device__ __forceinline__ void sts32(uint32_t addr, uint32_t v) { asm volatile("st.shared.u32 [%0], %1;" ::"r"(addr), "r"(v) : "memory"); }
__device__ __forceinline__ void sts32f(uint32_t addr, float v) { asm volatile("st.shared.f32 [%0], %1;" ::"r"(addr), "f"(v) : "memory"); }
__device__ __forceinline__ uint32_t lds32(uint32_t addr) { uint32_t v; asm volatile("ld.shared.u32 %0, [%1];" : "=r"(v) : "r"(addr) : "memory"); return v; }
__device__ __forceinline__ float lds32f(uint32_t addr) { float v; asm volatile("ld.shared.f32 %0, [%1];" : "=f"(v) : "r"(addr) : "memory"); return v; }
__device__ __forceinline__ void sts128(uint32_t addr, uint4 v) { asm volatile("st.shared.v4.u32 [%0], {%1,%2,%3,%4};" ::"r"(addr), "r"(v.x), "r"(v.y), "r"(v.z), "r"(v.w) : "memory"); }
__device__ __forceinline__ void st_async4(uint32_t raddr, uint32_t a, uint32_t b, uint32_t c, uint32_t d, uint32_t rbar) {
  asm volatile("st.async.shared::cluster.mbarrier::complete_tx::bytes.v4.b32 [%0], {%1,%2,%3,%4}, [%5];" ::"r"(raddr), "r"(a), "r"(b), "r"(c), "r"(d), "r"(rbar) : "memory");
}
__device__ __forceinline__ void st_async2(uint32_t raddr, uint32_t a, uint32_t b, uint32_t rbar) {
  asm volatile("st.async.shared::cluster.mbarrier::complete_tx::bytes.v2.b32 [%0], {%1,%2}, [%3];" ::"r"(raddr), "r"(a), "r"(b), "r"(rbar) : "memory");
}
__device__ __forceinline__ uint32_t pack2(float lo, float hi) { uint32_t r; asm("cvt.rn.bf16x2.f32 %0, %1, %2;" : "=r"(r) : "f"(hi), "f"(lo)); return r; }
__device__ __forceinline__ float bf_lo(uint32_t w) { return __uint_as_float(w << 16); }
__device__ __forceinline__ float bf_hi(uint32_t w) { return __uint_as_float(w & 0xFFFF0000u); }
__device__ __forceinline__ uint32_t hfma2(uint32_t a, uint32_t b, uint32_t c) { uint32_t r; asm("fma.rn.bf16x2 %0, %1, %2, %3;" : "=r"(r) : "r"(a), "r"(b), "r"(c)); return r; }
__device__ __forceinline__ uint32_t hmul2(uint32_t a, uint32_t b) { uint32_t r; asm("mul.rn.bf16x2 %0, %1, %2;" : "=r"(r) : "r"(a), "r"(b)); return r; }
__device__ __forceinline__ uint32_t hsub2(uint32_t a, uint32_t b) { uint32_t r; asm("sub.rn.bf16x2 %0, %1, %2;" : "=r"(r) : "r"(a), "r"(b)); return r; }
__device__ __forceinline__ float ex2v(float x) { float r; asm volatile("ex2.approx.ftz.f32 %0, %1;" : "=f"(r) : "f"(x)); return r; }
__device__ __forceinline__ void stg128(void* p, uint4 v) { asm volatile("st.global.v4.u32 [%0], {%1,%2,%3,%4};" ::"l"(p), "r"(v.x), "r"(v.y), "r"(v.z), "r"(v.w) : "memory"); }
__device__ __forceinline__ uint32_t hadd2(uint32_t a, uint32_t b) { uint32_t r; asm("add.rn.bf16x2 %0, %1, %2;" : "=r"(r) : "r"(a), "r"(b)); return r; }
__device__ __forceinline__ float ex2(float x) { float r; asm("ex2.approx.ftz.f32 %0, %1;" : "=f"(r) : "f"(x)); return r; }
__device__ __forceinline__ float gelu_h(float y) {
  float u = y * fmaf(8.f * 0.0356774081f, y * y, 2.f * 0.7978845608f), t;
  asm("tanh.approx.f32 %0, %1;" : "=f"(t) : "f"(u));
  return fmaf(y, t, y);
}
__device__ __forceinline__ float quad_sum(float v) { v += __shfl_xor_sync(~0u, v, 1); v += __shfl_xor_sync(~0u, v, 2); return v; }
__device__ __forceinline__ float quad_max(float v) { v = fmaxf(v, __shfl_xor_sync(~0u, v, 1)); v = fmaxf(v, __shfl_xor_sync(~0u, v, 2)); return v; }
__device__ __forceinline__ void rowsum_mma(float* c, const uint32_t* a) {
  asm volatile("mma.sync.aligned.m16n8k16.row.col.f32.bf16.bf16.f32 {%0,%1,%2,%3}, {%4,%5,%6,%7}, {%8,%8}, {%0,%1,%2,%3};"
               : "+f"(c[0]), "+f"(c[1]), "+f"(c[2]), "+f"(c[3]) : "r"(a[0]), "r"(a[1]), "r"(a[2]), "r"(a[3]), "r"(0x3F803F80u));
}
__device__ __forceinline__ void wg_fence() { asm volatile("wgmma.fence.sync.aligned;" ::: "memory"); }
__device__ __forceinline__ void wg_commit() { asm volatile("wgmma.commit_group.sync.aligned;" ::: "memory"); }
template <int N> __device__ __forceinline__ void wg_wait() { asm volatile("wgmma.wait_group.sync.aligned %0;" ::"n"(N) : "memory"); }
constexpr uint32_t SMEM0 = 1024;
__device__ __forceinline__ uint64_t desc(uint32_t rt16, uint32_t off, uint32_t lbo) {
  return (uint64_t)(rt16 + (((SMEM0 + off) >> 4) | ((lbo >> 4) << 16))) | ((uint64_t)0x40000040u << 32);
}
template <int N> __device__ __forceinline__ void keep(float* d) {
#pragma unroll
  for (int i = 0; i < N; i++) asm volatile("" : "+f"(d[i]));
}

template <int TB> __device__ __forceinline__ void wg_rs32(float* d, const uint32_t* a, uint64_t db, int sd) {
  asm volatile("{\n.reg .pred p;\nsetp.ne.b32 p, %21, 0;\n"
    "wgmma.mma_async.sync.aligned.m64n32k16.f32.bf16.bf16 {%0, %1, %2, %3, %4, %5, %6, %7, %8, %9, %10, %11, %12, %13, %14, %15}, {%16, %17, %18, %19}, %20, p, 1, 1, %22;\n}"
    : "+f"(d[0]), "+f"(d[1]), "+f"(d[2]), "+f"(d[3]), "+f"(d[4]), "+f"(d[5]), "+f"(d[6]), "+f"(d[7]), "+f"(d[8]), "+f"(d[9]), "+f"(d[10]), "+f"(d[11]), "+f"(d[12]), "+f"(d[13]), "+f"(d[14]), "+f"(d[15])
    : "r"(a[0]), "r"(a[1]), "r"(a[2]), "r"(a[3]), "l"(db), "r"(sd), "n"(TB));
}
template <int TB> __device__ __forceinline__ void wg_rs56(float* d, const uint32_t* a, uint64_t db, int sd) {
  asm volatile("{\n.reg .pred p;\nsetp.ne.b32 p, %33, 0;\n"
    "wgmma.mma_async.sync.aligned.m64n56k16.f32.bf16.bf16 {%0, %1, %2, %3, %4, %5, %6, %7, %8, %9, %10, %11, %12, %13, %14, %15, %16, %17, %18, %19, %20, %21, %22, %23, %24, %25, %26, %27}, {%28, %29, %30, %31}, %32, p, 1, 1, %34;\n}"
    : "+f"(d[0]), "+f"(d[1]), "+f"(d[2]), "+f"(d[3]), "+f"(d[4]), "+f"(d[5]), "+f"(d[6]), "+f"(d[7]), "+f"(d[8]), "+f"(d[9]), "+f"(d[10]), "+f"(d[11]), "+f"(d[12]), "+f"(d[13]), "+f"(d[14]), "+f"(d[15]), "+f"(d[16]), "+f"(d[17]), "+f"(d[18]), "+f"(d[19]), "+f"(d[20]), "+f"(d[21]), "+f"(d[22]), "+f"(d[23]), "+f"(d[24]), "+f"(d[25]), "+f"(d[26]), "+f"(d[27])
    : "r"(a[0]), "r"(a[1]), "r"(a[2]), "r"(a[3]), "l"(db), "r"(sd), "n"(TB));
}
template <int TB> __device__ __forceinline__ void wg_rs64(float* d, const uint32_t* a, uint64_t db, int sd) {
  asm volatile("{\n.reg .pred p;\nsetp.ne.b32 p, %37, 0;\n"
    "wgmma.mma_async.sync.aligned.m64n64k16.f32.bf16.bf16 {%0, %1, %2, %3, %4, %5, %6, %7, %8, %9, %10, %11, %12, %13, %14, %15, %16, %17, %18, %19, %20, %21, %22, %23, %24, %25, %26, %27, %28, %29, %30, %31}, {%32, %33, %34, %35}, %36, p, 1, 1, %38;\n}"
    : "+f"(d[0]), "+f"(d[1]), "+f"(d[2]), "+f"(d[3]), "+f"(d[4]), "+f"(d[5]), "+f"(d[6]), "+f"(d[7]), "+f"(d[8]), "+f"(d[9]), "+f"(d[10]), "+f"(d[11]), "+f"(d[12]), "+f"(d[13]), "+f"(d[14]), "+f"(d[15]), "+f"(d[16]), "+f"(d[17]), "+f"(d[18]), "+f"(d[19]), "+f"(d[20]), "+f"(d[21]), "+f"(d[22]), "+f"(d[23]), "+f"(d[24]), "+f"(d[25]), "+f"(d[26]), "+f"(d[27]), "+f"(d[28]), "+f"(d[29]), "+f"(d[30]), "+f"(d[31])
    : "r"(a[0]), "r"(a[1]), "r"(a[2]), "r"(a[3]), "l"(db), "r"(sd), "n"(TB));
}
template <int TB> __device__ __forceinline__ void wg_rs112(float* d, const uint32_t* a, uint64_t db, int sd) {
  asm volatile("{\n.reg .pred p;\nsetp.ne.b32 p, %61, 0;\n"
    "wgmma.mma_async.sync.aligned.m64n112k16.f32.bf16.bf16 {%0, %1, %2, %3, %4, %5, %6, %7, %8, %9, %10, %11, %12, %13, %14, %15, %16, %17, %18, %19, %20, %21, %22, %23, %24, %25, %26, %27, %28, %29, %30, %31, %32, %33, %34, %35, %36, %37, %38, %39, %40, %41, %42, %43, %44, %45, %46, %47, %48, %49, %50, %51, %52, %53, %54, %55}, {%56, %57, %58, %59}, %60, p, 1, 1, %62;\n}"
    : "+f"(d[0]), "+f"(d[1]), "+f"(d[2]), "+f"(d[3]), "+f"(d[4]), "+f"(d[5]), "+f"(d[6]), "+f"(d[7]), "+f"(d[8]), "+f"(d[9]), "+f"(d[10]), "+f"(d[11]), "+f"(d[12]), "+f"(d[13]), "+f"(d[14]), "+f"(d[15]), "+f"(d[16]), "+f"(d[17]), "+f"(d[18]), "+f"(d[19]), "+f"(d[20]), "+f"(d[21]), "+f"(d[22]), "+f"(d[23]), "+f"(d[24]), "+f"(d[25]), "+f"(d[26]), "+f"(d[27]), "+f"(d[28]), "+f"(d[29]), "+f"(d[30]), "+f"(d[31]), "+f"(d[32]), "+f"(d[33]), "+f"(d[34]), "+f"(d[35]), "+f"(d[36]), "+f"(d[37]), "+f"(d[38]), "+f"(d[39]), "+f"(d[40]), "+f"(d[41]), "+f"(d[42]), "+f"(d[43]), "+f"(d[44]), "+f"(d[45]), "+f"(d[46]), "+f"(d[47]), "+f"(d[48]), "+f"(d[49]), "+f"(d[50]), "+f"(d[51]), "+f"(d[52]), "+f"(d[53]), "+f"(d[54]), "+f"(d[55])
    : "r"(a[0]), "r"(a[1]), "r"(a[2]), "r"(a[3]), "l"(db), "r"(sd), "n"(TB));
}
template <int TB> __device__ __forceinline__ void wg_rs192(float* d, const uint32_t* a, uint64_t db, int sd) {
  asm volatile("{\n.reg .pred p;\nsetp.ne.b32 p, %101, 0;\n"
    "wgmma.mma_async.sync.aligned.m64n192k16.f32.bf16.bf16 {%0, %1, %2, %3, %4, %5, %6, %7, %8, %9, %10, %11, %12, %13, %14, %15, %16, %17, %18, %19, %20, %21, %22, %23, %24, %25, %26, %27, %28, %29, %30, %31, %32, %33, %34, %35, %36, %37, %38, %39, %40, %41, %42, %43, %44, %45, %46, %47, %48, %49, %50, %51, %52, %53, %54, %55, %56, %57, %58, %59, %60, %61, %62, %63, %64, %65, %66, %67, %68, %69, %70, %71, %72, %73, %74, %75, %76, %77, %78, %79, %80, %81, %82, %83, %84, %85, %86, %87, %88, %89, %90, %91, %92, %93, %94, %95}, {%96, %97, %98, %99}, %100, p, 1, 1, %102;\n}"
    : "+f"(d[0]), "+f"(d[1]), "+f"(d[2]), "+f"(d[3]), "+f"(d[4]), "+f"(d[5]), "+f"(d[6]), "+f"(d[7]), "+f"(d[8]), "+f"(d[9]), "+f"(d[10]), "+f"(d[11]), "+f"(d[12]), "+f"(d[13]), "+f"(d[14]), "+f"(d[15]), "+f"(d[16]), "+f"(d[17]), "+f"(d[18]), "+f"(d[19]), "+f"(d[20]), "+f"(d[21]), "+f"(d[22]), "+f"(d[23]), "+f"(d[24]), "+f"(d[25]), "+f"(d[26]), "+f"(d[27]), "+f"(d[28]), "+f"(d[29]), "+f"(d[30]), "+f"(d[31]), "+f"(d[32]), "+f"(d[33]), "+f"(d[34]), "+f"(d[35]), "+f"(d[36]), "+f"(d[37]), "+f"(d[38]), "+f"(d[39]), "+f"(d[40]), "+f"(d[41]), "+f"(d[42]), "+f"(d[43]), "+f"(d[44]), "+f"(d[45]), "+f"(d[46]), "+f"(d[47]), "+f"(d[48]), "+f"(d[49]), "+f"(d[50]), "+f"(d[51]), "+f"(d[52]), "+f"(d[53]), "+f"(d[54]), "+f"(d[55]), "+f"(d[56]), "+f"(d[57]), "+f"(d[58]), "+f"(d[59]), "+f"(d[60]), "+f"(d[61]), "+f"(d[62]), "+f"(d[63]), "+f"(d[64]), "+f"(d[65]), "+f"(d[66]), "+f"(d[67]), "+f"(d[68]), "+f"(d[69]), "+f"(d[70]), "+f"(d[71]), "+f"(d[72]), "+f"(d[73]), "+f"(d[74]), "+f"(d[75]), "+f"(d[76]), "+f"(d[77]), "+f"(d[78]), "+f"(d[79]), "+f"(d[80]), "+f"(d[81]), "+f"(d[82]), "+f"(d[83]), "+f"(d[84]), "+f"(d[85]), "+f"(d[86]), "+f"(d[87]), "+f"(d[88]), "+f"(d[89]), "+f"(d[90]), "+f"(d[91]), "+f"(d[92]), "+f"(d[93]), "+f"(d[94]), "+f"(d[95])
    : "r"(a[0]), "r"(a[1]), "r"(a[2]), "r"(a[3]), "l"(db), "r"(sd), "n"(TB));
}
template <int TB> __device__ __forceinline__ void wg_rs232(float* d, const uint32_t* a, uint64_t db, int sd) {
  asm volatile("{\n.reg .pred p;\nsetp.ne.b32 p, %121, 0;\n"
    "wgmma.mma_async.sync.aligned.m64n232k16.f32.bf16.bf16 {%0, %1, %2, %3, %4, %5, %6, %7, %8, %9, %10, %11, %12, %13, %14, %15, %16, %17, %18, %19, %20, %21, %22, %23, %24, %25, %26, %27, %28, %29, %30, %31, %32, %33, %34, %35, %36, %37, %38, %39, %40, %41, %42, %43, %44, %45, %46, %47, %48, %49, %50, %51, %52, %53, %54, %55, %56, %57, %58, %59, %60, %61, %62, %63, %64, %65, %66, %67, %68, %69, %70, %71, %72, %73, %74, %75, %76, %77, %78, %79, %80, %81, %82, %83, %84, %85, %86, %87, %88, %89, %90, %91, %92, %93, %94, %95, %96, %97, %98, %99, %100, %101, %102, %103, %104, %105, %106, %107, %108, %109, %110, %111, %112, %113, %114, %115}, {%116, %117, %118, %119}, %120, p, 1, 1, %122;\n}"
    : "+f"(d[0]), "+f"(d[1]), "+f"(d[2]), "+f"(d[3]), "+f"(d[4]), "+f"(d[5]), "+f"(d[6]), "+f"(d[7]), "+f"(d[8]), "+f"(d[9]), "+f"(d[10]), "+f"(d[11]), "+f"(d[12]), "+f"(d[13]), "+f"(d[14]), "+f"(d[15]), "+f"(d[16]), "+f"(d[17]), "+f"(d[18]), "+f"(d[19]), "+f"(d[20]), "+f"(d[21]), "+f"(d[22]), "+f"(d[23]), "+f"(d[24]), "+f"(d[25]), "+f"(d[26]), "+f"(d[27]), "+f"(d[28]), "+f"(d[29]), "+f"(d[30]), "+f"(d[31]), "+f"(d[32]), "+f"(d[33]), "+f"(d[34]), "+f"(d[35]), "+f"(d[36]), "+f"(d[37]), "+f"(d[38]), "+f"(d[39]), "+f"(d[40]), "+f"(d[41]), "+f"(d[42]), "+f"(d[43]), "+f"(d[44]), "+f"(d[45]), "+f"(d[46]), "+f"(d[47]), "+f"(d[48]), "+f"(d[49]), "+f"(d[50]), "+f"(d[51]), "+f"(d[52]), "+f"(d[53]), "+f"(d[54]), "+f"(d[55]), "+f"(d[56]), "+f"(d[57]), "+f"(d[58]), "+f"(d[59]), "+f"(d[60]), "+f"(d[61]), "+f"(d[62]), "+f"(d[63]), "+f"(d[64]), "+f"(d[65]), "+f"(d[66]), "+f"(d[67]), "+f"(d[68]), "+f"(d[69]), "+f"(d[70]), "+f"(d[71]), "+f"(d[72]), "+f"(d[73]), "+f"(d[74]), "+f"(d[75]), "+f"(d[76]), "+f"(d[77]), "+f"(d[78]), "+f"(d[79]), "+f"(d[80]), "+f"(d[81]), "+f"(d[82]), "+f"(d[83]), "+f"(d[84]), "+f"(d[85]), "+f"(d[86]), "+f"(d[87]), "+f"(d[88]), "+f"(d[89]), "+f"(d[90]), "+f"(d[91]), "+f"(d[92]), "+f"(d[93]), "+f"(d[94]), "+f"(d[95]), "+f"(d[96]), "+f"(d[97]), "+f"(d[98]), "+f"(d[99]), "+f"(d[100]), "+f"(d[101]), "+f"(d[102]), "+f"(d[103]), "+f"(d[104]), "+f"(d[105]), "+f"(d[106]), "+f"(d[107]), "+f"(d[108]), "+f"(d[109]), "+f"(d[110]), "+f"(d[111]), "+f"(d[112]), "+f"(d[113]), "+f"(d[114]), "+f"(d[115])
    : "r"(a[0]), "r"(a[1]), "r"(a[2]), "r"(a[3]), "l"(db), "r"(sd), "n"(TB));
}
template <int TB> __device__ __forceinline__ void wg_ss56(float* d, uint64_t da, uint64_t db, int sd) {
  asm volatile("{\n.reg .pred p;\nsetp.ne.b32 p, %30, 0;\n"
    "wgmma.mma_async.sync.aligned.m64n56k16.f32.bf16.bf16 {%0, %1, %2, %3, %4, %5, %6, %7, %8, %9, %10, %11, %12, %13, %14, %15, %16, %17, %18, %19, %20, %21, %22, %23, %24, %25, %26, %27}, %28, %29, p, 1, 1, 0, %31;\n}"
    : "+f"(d[0]), "+f"(d[1]), "+f"(d[2]), "+f"(d[3]), "+f"(d[4]), "+f"(d[5]), "+f"(d[6]), "+f"(d[7]), "+f"(d[8]), "+f"(d[9]), "+f"(d[10]), "+f"(d[11]), "+f"(d[12]), "+f"(d[13]), "+f"(d[14]), "+f"(d[15]), "+f"(d[16]), "+f"(d[17]), "+f"(d[18]), "+f"(d[19]), "+f"(d[20]), "+f"(d[21]), "+f"(d[22]), "+f"(d[23]), "+f"(d[24]), "+f"(d[25]), "+f"(d[26]), "+f"(d[27])
    : "l"(da), "l"(db), "r"(sd), "n"(TB));
}


__device__ __forceinline__ int perm448(int k) { return (k >> 5) * 32 + ((k & 7) >> 1) * 8 + ((k >> 4) & 1) * 4 + ((k >> 3) & 1) * 2 + (k & 1); }
__device__ __forceinline__ int perm64(int k) { return ((k & 7) >> 1) * 16 + (k >> 4) * 4 + ((k >> 3) & 1) * 2 + (k & 1); }

__device__ __forceinline__ float rcp(float x) { float r; asm("rcp.approx.ftz.f32 %0, %1;" : "=f"(r) : "f"(x)); return r; }
__device__ __forceinline__ float silu_bf(float c) { return bf_lo(pack2(c * rcp(1.f + ex2(-1.4426950408889634f * c)), 0.f)); }
__device__ __forceinline__ void fma8(float* acc, uint4 w, float s) {
  acc[0] = fmaf(bf_lo(w.x), s, acc[0]); acc[1] = fmaf(bf_hi(w.x), s, acc[1]);
  acc[2] = fmaf(bf_lo(w.y), s, acc[2]); acc[3] = fmaf(bf_hi(w.y), s, acc[3]);
  acc[4] = fmaf(bf_lo(w.z), s, acc[4]); acc[5] = fmaf(bf_hi(w.z), s, acc[5]);
  acc[6] = fmaf(bf_lo(w.w), s, acc[6]); acc[7] = fmaf(bf_hi(w.w), s, acc[7]);
}
__device__ __forceinline__ float warp_red8(float* v, int lane) {
  bool b4 = lane & 16, b3 = lane & 8, b2 = lane & 4;
  float t[4];
#pragma unroll
  for (int i = 0; i < 4; i++) { float keepv = b4 ? v[i + 4] : v[i], send = b4 ? v[i] : v[i + 4]; t[i] = keepv + __shfl_xor_sync(~0u, send, 16); }
  float u[2];
#pragma unroll
  for (int i = 0; i < 2; i++) { float keepv = b3 ? t[i + 2] : t[i], send = b3 ? t[i] : t[i + 2]; u[i] = keepv + __shfl_xor_sync(~0u, send, 8); }
  float keepv = b2 ? u[1] : u[0], send = b2 ? u[0] : u[1];
  float r = keepv + __shfl_xor_sync(~0u, send, 4);
  r += __shfl_xor_sync(~0u, r, 2);
  r += __shfl_xor_sync(~0u, r, 1);
  return r;
}

template <int NT> __device__ __forceinline__ void stage_rows(const uint32_t* w, uint32_t stg, int lane) {
  const uint32_t sa = stg + (lane & 15) * (NT * 16) + (lane >> 4) * 16;
#pragma unroll
  for (int t = 0; t + 1 < NT; t += 2) stsm4(sa + t * 16, w[2 * t], w[2 * t + 1], w[2 * t + 2], w[2 * t + 3]);
  if (NT & 1) stsm2(sa + (NT - 1) * 16, w[2 * NT - 2], w[2 * NT - 1]);
}
template <int NT> __device__ __forceinline__ void store_cm(const uint32_t* w, __nv_bfloat16* p) {
#pragma unroll
  for (int t = 0; t < NT; t++) { *(uint32_t*)(p + t * 512) = w[2 * t]; *(uint32_t*)(p + t * 512 + 64) = w[2 * t + 1]; }
}
template <int NT> __device__ __forceinline__ void store_rows(const uint32_t* w, uint32_t stg, __nv_bfloat16* gp, int pitch, int lane) {
  stage_rows<NT>(w, stg, lane);
  __syncwarp();
  {
    const int r = (lane * 37) >> 8, c = lane - 7 * r;
    gp += r * pitch + c * 8;
    if (lane < 28) {
#pragma unroll
      for (int k = 0; k < 4; k++) stg128(gp + 4 * k * pitch, lds128(stg + lane * 16 + k * 448));
    }
  }
}
__device__ __forceinline__ int st2pos(int h) { return ((h >> 4) * 16 + (h & 1) * 8 + ((h >> 1) & 7)) * 64; }
__device__ __forceinline__ uint32_t mod_bad(uint4 v, uint32_t tag) { return (v.x ^ tag) | (v.y ^ tag) | (v.z ^ tag) | (v.w ^ tag); }
__device__ __forceinline__ void put_mod4(uint32_t base, int i, uint4 v, uint32_t s2) {
  const bool isc = i >= 112;
  const float one = isc ? 1.f : 0.f;
  const int k = (isc ? i - 112 : i) * 4;
  base += (isc ? 0 : 896) + perm448(k) * 2;
  sts32(base, hmul2(pack2(bf_lo(v.x) + one, bf_lo(v.y) + one), s2));
  sts32(base + 16, hmul2(pack2(bf_lo(v.z) + one, bf_lo(v.w) + one), s2));
}

__host__ __device__ constexpr uint32_t bar_count(int i) { return i >= B_CNT8 ? 8 : i >= B_CNT4 ? 4 : i >= B_CNT2 ? 2 : 1; }
constexpr uint32_t WE(int wait, int p0, int p1, int full, int c, int type, int add, int n) {
  return (uint32_t)wait | p0 << 8 | p1 << 13 | full << 18 | c << 22 | type << 25 | add << 27 | (uint32_t)n << 29;
}
__constant__ uint32_t c_wprog[21] = {
  WE(B_VALL, 20, 21, B_WO, 4, 1, 0, 7), WE(0, 22, 23, B_WO, 5, 1, 0, 0), WE(0, 24, 25, B_WO, 6, 1, 0, 0),
  WE(B_QPASS, 0, 1, B_WO, 0, 1, 0, 0), WE(0, 2, 3, B_WO, 1, 1, 0, 0), WE(0, 4, 5, B_WO, 2, 1, 0, 0), WE(0, 6, 7, B_WO, 3, 1, 0, 0),
  WE(PH1 + B_A3 + 6, 16, 17, B_Z2W, 0, 2, 2, 3), WE(0, 18, 19, B_Z2W, 1, 2, 2, 0), WE(B_S3MMA, 15, 26, B_Z2W, 2, 2, 2, 0),
  WE(B_A4 + 5, 20, 21, B_Z2W + 1, 3, 2, 2, 3), WE(0, 22, 23, B_Z2W + 1, 4, 2, 2, 0), WE(0, 24, 25, B_Z2W + 1, 5, 2, 2, 0),
  WE(B_A4E, 0, 1, B_Z2W + 2, 6, 2, 2, 1),
  WE(B_A4RD, 4, 5, B_Z1W, 0, 2, 0, 2), WE(B_A4RD + 1, 6, 14, B_Z1W, 1, 2, 0, 0),
  WE(0, 9, 10, B_Z1W + 1, 2, 2, 0, 2), WE(0, 11, 12, B_Z1W + 1, 3, 2, 0, 0),
  WE(B_Z2C, 16, 17, B_Z1W + 2, 4, 2, 0, 3), WE(0, 18, 19, B_Z1W + 2, 5, 2, 0, 0), WE(B_Z2PASS, 0, 1, B_Z1W + 2, 6, 2, 0, 0)};

__global__ void __cluster_dims__(2, 1, 1) __launch_bounds__(384, 1) fused_kernel(const __grid_constant__ Params P) {
  extern __shared__ __align__(1024) uint8_t smem_raw[];
  const uint32_t sb = smem_u32(smem_raw);
  const int tid = threadIdx.x, lane = tid & 31, warp = __shfl_sync(~0u, tid >> 5, 0);
  const int b = blockIdx.x, rb = b >> 3, c8 = b & 7, cb4 = c8 >> 1, kh = c8 & 1;
  const int h3 = 2 * rb + (cb4 & 1), c4 = 2 * (cb4 >> 1) + kh;
  const int rb1 = 2 * (b >> 4) + kh, j1 = (b >> 1) & 7, b1 = rb1 * 8 + j1;
  const uint32_t peer = kh ^ 1;
  int bud = 1 << 20;
  auto BAR = [&](int i) { return sb + OFF_BAR + 8u * i; };
  auto PAGE = [&](int i) { return sb + PG * i; };
  auto mbar_wait = [&](uint32_t bar, uint32_t par = 0) { mbar_wait2(bar, par, bud); };
  auto poll = [&](int c, uint32_t target) { while (!__all_sync(~0u, reached(c, target)) && --bud > 0) {} fence_async_glob(); };

  if (blockIdx.x >= 128) {
    float* tab = (float*)(smem_raw + 200704);
    const int rg = min(tid / 56, 5), cg = tid - 56 * (tid / 56), col0 = 448 * (b - 126);
    if (tid == 0) { mbar_init(BAR(0), 1); fence_async_smem(); }
    __syncthreads();
    const uint32_t tg = (ld_relaxed(&g_epoch) + 1) << 16;
    float acc[8] = {0, 0, 0, 0, 0, 0, 0, 0};
#pragma unroll 1
    for (int h = 0; h < 2; h++) {
      if (warp == 0) {
        e_expect(BAR(0), 200704);
        e_tma2d(sb, &P.wmods, col0, 224 * h, BAR(0));
        e_tma2d(sb + 100352, &P.wmods, col0 + 224, 224 * h, BAR(0));
      }
      if (tid < 224) tab[tid] = silu_bf(bf_lo(__ldg((const uint16_t*)P.pc + 224 * h + tid)));
      __syncthreads();
      mbar_wait(BAR(0), h);
#pragma unroll 2
      for (int k = rg; k < 224; k += 6) fma8(acc, lds128(sb + (cg >= 28 ? 100352 - 448 : 0) + k * 448 + cg * 16), tab[k]);
      __syncthreads();
    }
    if (tid < 336) {
#pragma unroll
      for (int i = 0; i < 8; i++) tab[512 + rg * 448 + cg * 8 + i] = acc[i];
    }
    __syncthreads();
    for (int c = tid; c < 448; c += 384) {
      float v = 0.f;
#pragma unroll
      for (int i = 0; i < 6; i++) v += tab[512 + i * 448 + c];
#pragma unroll 1
      for (int r = 0; r < MODREP; r++) st_relaxed(&g_mod[r * 2688 + col0 + c], (pack2(v, 0.f) & 0xFFFFu) | tg);
    }
    return;
  }
  if ((sb & 0xFFFFFFu) != SMEM0) bud = 0;
  uint32_t ep = 0;
  if (warp <= 8) {
    if (lane == 0) {
      const uint32_t cnt = bar_count(12 * warp);
#pragma unroll
      for (int i = 0; i < 12; i++) mbar_init(BAR(12 * warp + i), cnt);
      asm volatile("fence.mbarrier_init.release.cluster;" ::: "memory");
    }
    __syncwarp();
    if (warp == 1) {
#pragma unroll
      for (int i = 0; i < 6; i++) e_expect(BAR(B_XB5 + i), i < 2 ? 14336 : i < 4 ? 7168 : 4096);
    }
    if (warp == 8) {
      asm volatile(ELECT("mbarrier.expect_tx.relaxed.cta.shared::cta.b64 [%0], %1;") ::"r"(BAR(B_KALL)), "r"(min(rb1, 2) * 16384) : "memory");
      asm volatile(ELECT("mbarrier.expect_tx.relaxed.cta.shared::cta.b64 [%0], %1;") ::"r"(BAR(B_VALL)), "r"(min(rb1, 2) * 16384) : "memory");
    }
    bar_arrive(10, 384);
    bar_sync(6, 288);
  }
  auto cluster_wait = [&]() { asm volatile("barrier.cluster.wait.acquire.aligned;" ::: "memory"); };
  auto cluster_arrive = [&]() { asm volatile("barrier.cluster.arrive.relaxed.aligned;" ::: "memory"); };

  if (warp >= 8) {
    asm volatile("setmaxnreg.dec.sync.aligned.u32 56;");
    auto rows_mc = [&](const __nv_bfloat16* src, int page, int bar, int par) {
#pragma unroll 1
      for (int c = par; c < 7; c += 2) e_bulk_ld_mc(PAGE(page + c), src + c * 4096, 8192, BAR(bar + c));
    };
    const int a = warp - 10, hh = 2 * rb + a;
    if (warp > 8) {
      const int t96 = tid - 288;
      {
        uint16_t cc[5];
#pragma unroll
        for (int q = 0; q < 5; q++) cc[q] = t96 + 96 * q < 448 ? __ldg((const uint16_t*)P.pc + t96 + 96 * q) : (uint16_t)0;
        const uint32_t e0 = ld_relaxed(&g_epoch);
        if (warp == 9 && lane < 10) prefetch_map(&P.wmod + lane);
        cluster_arrive();
        bar_sync(10, 384);
        mbar_wait(BAR(B_MW));
        float acc[8] = {0, 0, 0, 0, 0, 0, 0, 0};
#pragma unroll
        for (int q = 0; q < 5; q++) fma8(acc, lds128(sb + OFF_MW + min(t96 + 96 * q, 447) * 16), silu_bf(bf_lo(cc[q])));
        ep = __shfl_sync(~0u, e0, 0) + 1;
        const float r = warp_red8(acc, lane);
        if (!(lane & 3)) sts32f(sb + OFF_RED + (warp - 9) * 32 + lane, r);
        bar_sync(9, 96);
        if (b < 112) {
          const uint32_t red = sb + OFF_RED + (t96 & 7) * 4;
          const uint32_t v = (pack2(lds32f(red) + lds32f(red + 32) + lds32f(red + 64), 0.f) & 0xFFFFu) | (ep << 16);
#pragma unroll 1
          for (int r = t96 >> 3; r < MODREP; r += 12) st_relaxed(&g_mod[r * 2688 + 8 * b + (t96 & 7)], v);
        }
      }
#pragma unroll 1
      for (int st = 0; st < 3; st++) {
        if (st != 1) {
          if (st && warp == 9) break;
          mbar_wait(BAR(st ? B_WO : B_X + 6));
          bool first = !st;
          const uint32_t* gm = g_mod + rb * 2688;
          const int nt = st ? 64 : 96, ni = st ? 265 : 223;
#pragma unroll 1
          for (int i0 = st ? t96 - 32 : t96; i0 <= ni; i0 += 192) {
            uint4 x[3];
            uint32_t bad;
            do {
              bad = 0;
#pragma unroll
              for (int q = 0; q < 3; q++) {
                const int i = min(i0 + nt * q, ni) - 224;
                x[q] = ld_relaxed4(&gm[i < 0 ? 672 * st + 896 + i * 4 : i < 28 ? 896 + 112 * c4 + i * 4 : 2240 - 112 + 56 * c8 + i * 4]);
              }
              if (first) { bar_arrive(11, 128); first = false; }
#pragma unroll
              for (int q = 0; q < 3; q++) bad |= mod_bad(x[q], ep << 16);
            } while (__any_sync(~0u, (bad >> 16) != 0) && --bud > 0);
#pragma unroll 1
            for (int q = 0; q < 3; q++) {
              const int i = min(i0 + nt * q, ni) - 224;
              if (i < 0) put_mod4(sb + (st ? OFF_MOD2 : OFF_MOD1), i + 224, x[0], st ? 0x3F003F00u : 0x3F803F80u);
              else { sts32(sb + OFF_GA + i * 8, __byte_perm(x[0].x, x[0].y, 0x5410)); sts32(sb + OFF_GA + i * 8 + 4, __byte_perm(x[0].z, x[0].w, 0x5410)); }
              x[0] = x[1]; x[1] = x[2];
            }
            if (!st) break;
          }
          __syncwarp();
          if (st) { asm volatile("fence.acq_rel.cta;" ::: "memory"); e_arrive(BAR(B_MOD2)); break; }
          __syncwarp();
          bar_arrive(1, 384);
          if (warp > 9) l2_prefetch(a ? (const uint8_t*)P.pwin + b * 12544 : (const uint8_t*)P.pwo + b * 3136, a ? 12544 : 3136, lane);
        }
        const int kv = st;
        if (warp > 9) {
          mbar_wait(BAR(B_KRDY + 2 * kv + a));
          e_bulk_st(g_kv + (size_t)(b1 * 2 + kv) * 16384 + a * 8192, PAGE(12 + 6 * kv + a), 8192);
          e_publish(C_K + 128 * kv + b1);
          continue;
        }
        const uint32_t dst = PAGE(8 + 6 * kv), bar = BAR(B_KALL + kv);
        mbar_wait(BAR(B_XFREE + kv));
        uint32_t todo = rb1 >= 2 ? 3 : rb1;
        while (todo) {
          const uint32_t m = (__ballot_sync(~0u, reached(C_K + 128 * kv + max(b1 - 8 - 8 * (lane & 1), 0), 2 * ep)) | (--bud <= 0 ? 3u : 0u)) & todo;
          if (!m) continue;
          fence_async_glob();
          const int d = (m & 1) ^ 1;
          e_bulk_ld(dst + (1 - d) * 16384, g_kv + (size_t)((b1 - 8 - 8 * d) * 2 + kv) * 16384, 16384, bar);
          todo &= ~(1u << d);
        }
      }
    }
    if (warp == 8) {
      e_expect(BAR(B_MW), 7168);
      e_tma2d(sb + OFF_MW, &P.wmod, 8 * min(b, 111), 0, BAR(B_MW));
      e_tma2d(sb + OFF_MW + 3584, &P.wmod, 8 * min(b, 111), 224, BAR(B_MW));
#pragma unroll
      for (int c = 0; c < 7; c++) { e_expect(BAR(B_X + c), 16384); e_tma2d(PAGE(2 * c), &P.x, 64 * c, 128 * rb1, BAR(B_X + c)); }
      cluster_arrive();
      cluster_wait();
#pragma unroll 1
      for (int p = 0; p < 3; p++) {
        const int col = (56 * j1 & ~15) + (p == 2 ? 0 : 448 + 448 * p);
        e_expect(BAR(B_WK + p), 7 * 8192);
        if (p == 0) bar_sync(11, 128);
        if (p == 1) bar_sync(1, 384);
#pragma unroll 1
        for (int c = (p ^ kh) & 1; c < 7; c += 2) {
          if (c + 7 * p >= 13 && c + 7 * p < 16) { mbar_wait(BAR(B_XFREE)); mbar_wait(BAR(B_XFREE2)); }
          e_tma2d_mc(c + 7 * p == 13 ? PAGE(7) : PAGE((p == 0 ? 14 : p == 1 ? 21 : 0) + c), &P.wqkv, col, 64 * c, BAR(B_WK + p));
        }
      }
#pragma unroll 1
      for (int i = 0; i < 21; i++) {
        if (i == 7) {
          asm volatile(ELECT("cp.async.bulk.prefetch.L2.global [%0], 32768;") ::"l"((const uint8_t*)P.pwsp + (size_t)b * 65536) : "memory");
          asm volatile(ELECT("cp.async.bulk.prefetch.L2.global [%0], 32768;") ::"l"((const uint8_t*)P.pwsp + (size_t)b * 65536 + 32768) : "memory");
        }
        const uint32_t e = c_wprog[i], type = (e >> 25) & 3;
        if (e & 255) mbar_wait(BAR(e & 127), (e >> 7) & 1);
        const uint32_t bar = BAR((e >> 18) & 15);
        const int col = 112 * (type == 1 ? c4 : c8) + 448 * ((e >> 27) & 3), row = 64 * ((e >> 22) & 7);
        const CUtensorMap* m = &P.wqkv + (2 * type - 1);
        if (e >> 29) e_expect(bar, (e >> 29) * 14336);
        e_tma2d(PAGE((e >> 8) & 31), m, col, row, bar);
        e_tma2d(PAGE((e >> 13) & 31), m + 1, col + (type == 1 ? 56 : 64), row, bar);
      }
#pragma unroll 1
      for (int q = 0; q < 4; q++) {
        if (q != 2) mbar_wait(BAR(B_KPASS + q - (q >> 1)), 1);
        const uint32_t bar = BAR(B_B6 + (q > 0)), dst = PAGE(2) + q * 28672;
        if (q < 2) e_expect(bar, q ? 3 * 25088 : 25088);
        e_tma2d(dst, &P.wout64, 112 * cb4, 112 * ((c8 + 2 * q) & 7), bar);
        e_tma2d(dst + 14336, &P.wout48, 112 * cb4 + 64, 112 * ((c8 + 2 * q) & 7), bar);
      }
    } else if (warp == 9) {
#pragma unroll
      for (int c = 0; c < 7; c++) e_expect(BAR(B_A3 + c), 8192);
      mbar_wait(BAR(B_ATT)); mbar_wait(BAR(B_ATT2));
      poll(C_O + h3, 8 * ep);
      rows_mc(g_o + h3 * 28672, 8, B_A3, kh);
      l2_prefetch((const uint8_t*)P.pwout + b * 6272, 6272, lane);
      mbar_wait(BAR(B_Z2PASS));
#pragma unroll 1
      for (int i = 0; i < 16; i++) {
        const int s = i & 3, h = 16 * kh + (i < 8 ? 2 * i : 2 * i - 15);
        if (i == 0 || i == 3) {
          poll(C_Z + 16 * kh + 2 * (lane & 7) + (i & 1), 8 * ep);
          e_bulk_ld(PAGE(26) + (i & 1) * 4096, g_st2 + (2 * kh + (i & 1)) * 512, 4096, BAR(B_RAW + (i & 1)));
        }
        if (i == 1) mbar_wait(BAR(B_STGDONE));
        if (i) mbar_wait(BAR(i >= 4 ? B_S5E + s : B_Z1C + i - 1), i >= 4 ? (i >> 2) - 1 & 1 : 0);
        const uint32_t dst = PAGE(s == 0 ? 20 : 6 * s - 4);
        const uint8_t* src = g_z2t + (size_t)h * FH * 128;
        e_expect(BAR(B_S5F + s), 46080);
        e_tma2d(dst, &P.wsp, 64 * h, 128 * rb, BAR(B_S5F + s));
        e_bulk_ld(dst + 16384, src + 14336 * c8, 14336, BAR(B_S5F + s));
        e_bulk_ld(dst + 30720, src + 14336 * (c8 ^ 1), 14336, BAR(B_S5F + s));
        e_bulk_ld(dst + 45056, g_s.zs + h * 1024, 1024, BAR(B_S5F + s));
      }
    } else {
#pragma unroll
      for (int c = 0; c < 7; c++) e_expect(BAR(B_A4 + 7 * a + c), c ? 8192 : 12288);
      mbar_wait(BAR(B_S3MMA)); mbar_wait(BAR(B_S3MMA2));
      poll(C_X + hh, 4 * ep);
      e_bulk_ld(sb + (a ? OFF_RAW1B : OFF_MW), g_st1 + hh * 512, 4096, BAR(B_A4 + 7 * a));
      rows_mc(g_x1 + hh * 28672, 7 * a, B_A4 + 7 * a, kh ^ a);
      bar_sync(12 + a, 160);
      e_release(C_Z + hh);
      e_arrive(BAR(B_STGDONE));
      mbar_wait(BAR(B_RAW + a));
#pragma unroll 1
      for (int q = 8 * a; q < 8 * a + 8; q++) {
        const uint4 v = lds128(PAGE(26) + q * 512 + lane * 16);
        const float m0 = __uint_as_float(v.x) * (1.f / 896.f), m1 = __uint_as_float(v.z) * (1.f / 896.f);
        const float r0 = rsqrtf(fmaxf(fmaf(__uint_as_float(v.y), 1.f / 896.f, -m0 * m0), 0.f) + 1e-5f);
        const float r1 = rsqrtf(fmaxf(fmaf(__uint_as_float(v.w), 1.f / 896.f, -m1 * m1), 0.f) + 1e-5f);
        sts32(sb + OFF_R5 + (q * 64 + perm64(2 * lane)) * 2, pack2(r0, r1));
      }
      asm volatile("fence.acq_rel.cta;" ::: "memory");
      e_arrive(BAR(B_ST2 + a));
      mbar_wait(BAR(B_QPASS), 1);
      poll(C_U + 2 * rb + kh, 4 * ep);
#pragma unroll 1
      for (int q = 1; q < 4; q++) {
        if (q == 3 && a) mbar_wait(BAR(B_XRD));
        e_expect(BAR(B_A4 + 7 * a + q), 14336);
        e_bulk_ld(PAGE(16) + (3 * a + q - 1) * 14336, g_u + (hh * 8 + ((c8 + 2 * q) & 7)) * 7168, 14336, BAR(B_A4 + 7 * a + q));
      }
    }
    __syncwarp();
    if (warp > 8) cluster_wait();
  } else {
    asm volatile("setmaxnreg.inc.sync.aligned.u32 224;");
    const int a = warp >> 2, w = warp & 3, j = lane & 3, g = lane >> 2;
    const int r0 = 16 * w + g;
    const uint32_t lx = lane & 7, lhi = lane >> 4;
    uint32_t lda[4];
#pragma unroll
    for (int ks = 0; ks < 4; ks++) lda[ks] = sb + (16 * w + (lane & 15)) * 128 + (((2 * ks + lhi) ^ lx) << 4);

    cluster_arrive();
    const uint32_t ldc = sb + lhi * 1024 + (16 * w + (lane & 15)) * 16;
    const int cmo = r0 * 8 + 2 * j;
    if (a == 1) bar_arrive(4, 256);

    uint32_t qf[14];
    {
      uint32_t A[28][4];
      {
        float s2[2][4] = {}, q2[2][4] = {};
        uint32_t pv0 = 0, pv1 = 0;
#pragma unroll
        for (int c = 0; c < 7; c++) {
          mbar_wait(BAR(B_X + c));
#pragma unroll
          for (int ks = 0; ks < 4; ks++) ldsm4(A[4 * c + ks], lda[ks] + a * PG + 2 * c * PG);
#pragma unroll
          for (int ks = 0; ks < 4; ks++) rowsum_mma(s2[ks & 1], A[4 * c + ks]);
          if (c == 0) {
            const float m0 = (s2[0][0] + s2[1][0]) * (1.f / 64.f), m1 = (s2[0][2] + s2[1][2]) * (1.f / 64.f);
            pv0 = pack2(m0, m0); pv1 = pack2(m1, m1);
          }
#pragma unroll
          for (int ks = 0; ks < 4; ks++) {
            uint32_t* x = A[4 * c + ks];
            x[0] = hsub2(x[0], pv0); x[1] = hsub2(x[1], pv1); x[2] = hsub2(x[2], pv0); x[3] = hsub2(x[3], pv1);
            uint32_t sq[4] = {hmul2(x[0], x[0]), hmul2(x[1], x[1]), hmul2(x[2], x[2]), hmul2(x[3], x[3])};
            rowsum_mma(q2[ks & 1], sq);
          }
        }
        const float m0 = fmaf(s2[0][0] + s2[1][0], 1.f / 448.f, -bf_lo(pv0)), m1 = fmaf(s2[0][2] + s2[1][2], 1.f / 448.f, -bf_lo(pv1));
        const float rs0 = rsqrtf(fmaxf(fmaf(q2[0][0] + q2[1][0], 1.f / 448.f, -m0 * m0), 0.f) + 1e-5f);
        const float rs1 = rsqrtf(fmaxf(fmaf(q2[0][2] + q2[1][2], 1.f / 448.f, -m1 * m1), 0.f) + 1e-5f);
        cluster_wait();
        e_arrive_dep(BAR(B_XFREE), __float_as_uint(rs0)); e_arrive_dep(mapa(BAR(B_XFREE2), peer), __float_as_uint(rs0));
        const uint32_t rp0 = pack2(rs0, rs0), rp1 = pack2(rs1, rs1), nm0 = pack2(-m0 * rs0, -m0 * rs0), nm1 = pack2(-m1 * rs1, -m1 * rs1);
#pragma unroll
        for (int i = 0; i < 28; i++) {
          A[i][0] = hfma2(A[i][0], rp0, nm0); A[i][1] = hfma2(A[i][1], rp1, nm1); A[i][2] = hfma2(A[i][2], rp0, nm0); A[i][3] = hfma2(A[i][3], rp1, nm1);
        }
      }
      bar_sync(1, 384);
      if (a == 1) bar_sync(7, 256);
#pragma unroll
      for (int h = 0; h < 14; h++) {
        uint4 cv = lds128(sb + OFF_MOD1 + j * 16 + h * 64), sv = lds128(sb + OFF_MOD1 + 896 + j * 16 + h * 64);
        uint32_t* p = A[2 * h]; uint32_t* q = A[2 * h + 1];
        p[0] = hfma2(p[0], cv.x, sv.x); p[1] = hfma2(p[1], cv.x, sv.x); p[2] = hfma2(p[2], cv.y, sv.y); p[3] = hfma2(p[3], cv.y, sv.y);
        q[0] = hfma2(q[0], cv.z, sv.z); q[1] = hfma2(q[1], cv.z, sv.z); q[2] = hfma2(q[2], cv.w, sv.w); q[3] = hfma2(q[3], cv.w, sv.w);
      }
      if (a == 0) asm volatile("bar.arrive 7, 256;" ::"r"(A[27][3]), "r"(A[20][0]), "r"(A[13][1]) : "memory");
      const uint32_t st_addr = sb + (12 + a) * PG + (16 * w + ((lane >> 3) & 1) * 8 + lx) * 128;
#pragma unroll 1
      for (int p = 0; p < 3; p++) {
        float acc[28];
        const uint32_t wb = (p == 0 ? 14 : p == 1 ? 21 : 0) * (PG / 16) + (j1 & 1), wb6 = p == 1 ? PG / 16 + (j1 & 1) : wb;
        mbar_wait(BAR(B_WK + p));
        bar_sync(4 + a, 256);
        wg_fence();
#pragma unroll
        for (int i = 0; i < 28; i++) wg_rs56<1>(acc, A[i], desc(i < 24 ? wb : wb6, i * 2048, 0), i != 0);
        wg_commit();
        if (p < 2 || a == 0) bar_arrive(5 - a, 256);
        wg_wait<0>(); keep<28>(acc);
        e_arrive(BAR(B_KPASS + p));
#pragma unroll
        for (int i = 0; i < 14; i++) qf[i] = pack2(acc[2 * i], acc[2 * i + 1]);
        if (p < 2) {
          if (p == 1 || rb1 < 2) mbar_wait(BAR(B_XFREE + p));
          if (rb1 < 2) {
#pragma unroll 1
            for (int i = tid; i < (2 - rb1) * 1024; i += 256) sts128(PAGE(8 + 6 * p) + i * 16, make_uint4(0, 0, 0, 0));
          }
          const uint32_t fill = (p == 1 && !(j & 1)) ? 0x3F80u : 0u;
          const uint32_t ta = st_addr + p * 6 * PG;
          stsm4(ta + ((lhi ^ lx) << 4), qf[0], qf[1], qf[2], qf[3]);
          stsm4(ta + (((2 + lhi) ^ lx) << 4), qf[4], qf[5], j < 2 ? qf[6] : fill, j < 2 ? qf[7] : fill);
          stsm4(ta + (((4 + lhi) ^ lx) << 4), j < 2 ? fill : qf[6], j < 2 ? fill : qf[7], qf[8], qf[9]);
          stsm4(ta + (((6 + lhi) ^ lx) << 4), qf[10], qf[11], qf[12], qf[13]);
          fence_async_smem();
          e_arrive(BAR(B_KRDY + 2 * p + a)); e_arrive(BAR(B_KALL + p));
        }
      }
    }
    {
      const int q0 = 128 * rb1 + 64 * a;
      const float sc = 0.18898223650461362f * 1.4426950408889634f;
      const float ninf = __int_as_float(0xff800000);
      uint32_t ow[14];
      const int dd = r0 - 2 * j;
      mbar_wait(BAR(B_KALL));
#pragma unroll 1
      for (int hd = 0; hd < 2; hd++) {
        const uint32_t kb = a * (PG / 16) + hd * 4;
        float sm[96], s0[32], s4[32];
        wg_fence();
#pragma unroll
        for (int ks = 0; ks < 2; ks++) {
          wg_rs64<0>(s0, qf + 4 * ks, desc(kb, 8 * PG + ks * 32, 16), ks);
          wg_rs64<0>(s4, qf + 4 * ks, desc(kb, 12 * PG + ks * 32, 16), ks);
          wg_rs192<0>(sm, qf + 4 * ks, desc(kb, 9 * PG + ks * 32, 16), ks);
        }
        wg_commit();
        wg_wait<0>(); keep<96>(sm); keep<32>(s0); keep<32>(s4);
#pragma unroll
        for (int i = 0; i < 8; i++) qf[i] = qf[i + 6];
        if (q0 < 256) {
#pragma unroll
          for (int i = 0; i < 32; i++) s0[i] = ninf;
        }
#pragma unroll
        for (int i = 0; i < 32; i++) { int t = i >> 2, e = (i >> 1) & 1, f = i & 1; s4[i] = (8 * t + f - 8 * e <= dd) ? s4[i] : s0[i]; }
        float mx[2] = {s4[0], s4[2]};
#pragma unroll
        for (int i = 0; i < 32; i++) mx[(i >> 1) & 1] = fmaxf(mx[(i >> 1) & 1], s4[i]);
#pragma unroll
        for (int k = 0; k < 3; k++) {
          float t[2] = {sm[32 * k], sm[32 * k + 2]};
#pragma unroll
          for (int i = 0; i < 32; i++) t[(i >> 1) & 1] = fmaxf(t[(i >> 1) & 1], sm[32 * k + i]);
          if (q0 - 192 + 64 * k >= 0) { mx[0] = fmaxf(mx[0], t[0]); mx[1] = fmaxf(mx[1], t[1]); }
        }
        mx[0] = -quad_max(mx[0]) * sc; mx[1] = -quad_max(mx[1]) * sc;
        if (hd | a) mbar_wait(BAR(B_TURN - 1 + 2 * hd + a));
        asm volatile("" : "+f"(mx[0]), "+f"(mx[1]) :: "memory");
        uint32_t pm[48], p0[16], p4[16];
#pragma unroll
        for (int k = 0; k < 3; k++) {
          const bool ok = q0 - 192 + 64 * k >= 0;
          const float m0 = ok ? mx[0] : ninf, m1 = ok ? mx[1] : ninf;
#pragma unroll
          for (int i = 16 * k; i < 16 * k + 16; i++) {
            const float m = (i & 1) ? m1 : m0;
            pm[i] = pack2(ex2v(fmaf(sm[2 * i], sc, m)), ex2v(fmaf(sm[2 * i + 1], sc, m)));
          }
        }
#pragma unroll
        for (int i = 0; i < 16; i++) {
          const uint32_t pw = pack2(ex2v(fmaf(s4[2 * i], sc, mx[i & 1])), ex2v(fmaf(s4[2 * i + 1], sc, mx[i & 1])));
          const int lim = 8 * (i >> 1) - 8 * (i & 1);
          const uint32_t mk = (lim + 1 <= dd) ? 0xFFFFFFFFu : (lim <= dd ? 0x0000FFFFu : 0u);
          p4[i] = pw & mk; p0[i] = pw & ~mk;
        }
        if (hd == 0 || a == 0) {
          const uint32_t dep = (pm[3] | pm[9] | pm[15]) | (pm[21] | pm[27] | pm[33]) | (pm[39] | pm[45] | p4[2]) | (p0[7] | p4[12] | p0[15]);
          __syncwarp();
          if (lane == 0) mbar_arrive(BAR(B_TURN + 2 * hd + a) + ((dep >> 31) << 3));
        }
        if (hd == 0) mbar_wait(BAR(B_VALL));
        float o[16];
        wg_fence();
#pragma unroll
        for (int s = 0; s < 12; s++) wg_rs32<1>(o, pm + 4 * s, desc(kb, 15 * PG + s * 2048, 0), s);
#pragma unroll
        for (int s = 0; s < 4; s++) wg_rs32<1>(o, p0 + 4 * s, desc(kb, 14 * PG + s * 2048, 0), 1);
#pragma unroll
        for (int s = 0; s < 4; s++) wg_rs32<1>(o, p4 + 4 * s, desc(kb, 18 * PG + s * 2048, 0), 1);
        wg_commit();
        wg_wait<0>(); keep<16>(o);
        const int src = (lane & 28) | (hd ? 0 : 2);
        const float l0 = rcp(__shfl_sync(~0u, hd ? o[0] : o[12], src)), l1 = rcp(__shfl_sync(~0u, hd ? o[2] : o[14], src));
        const bool keep3 = hd == 1 && j < 2;
        const uint32_t e0 = ow[12], e1 = ow[13];
#pragma unroll
        for (int i = 0; i < 6; i++) ow[i] = ow[i + 6];
#pragma unroll
        for (int t = 0; t < 4; t++) { ow[6 + 2 * t] = pack2(o[4 * t] * l0, o[4 * t + 1] * l0); ow[7 + 2 * t] = pack2(o[4 * t + 2] * l1, o[4 * t + 3] * l1); }
        ow[6] = keep3 ? e0 : ow[6]; ow[7] = keep3 ? e1 : ow[7];
      }
      store_cm<7>(ow, g_o + ((2 * rb1 + a) * 56 + 7 * j1) * 512 + cmo);
      if (w == 0 && lane < 4) stg128(g_st2 + st2pos(2 * rb1 + a) + 8 * j1 + 2 * lane, make_uint4(0, 0, 0, 0));
      e_arrive(BAR(B_ATT)); e_arrive_remote(mapa(BAR(B_ATT2), peer));
      bar_sync(2 + a, 128);
      if (w == 0) e_release(C_O + 2 * rb1 + a);
    }
    {
      uint32_t xr[16];
      {
        const int rr = (lane * 37) >> 8, cc = lane - 7 * rr;
        const uint32_t stg = PAGE(26) + warp * 1024;
        uint4 v[4];
        if (lane < 28) {
#pragma unroll
          for (int k = 0; k < 4; k++) v[k] = __ldg((const uint4*)(P.px + (size_t)(64 * h3 + 16 * w + 4 * k + rr) * DM + 112 * c4 + 56 * a) + cc);
        }
#pragma unroll
        for (int hf = 0; hf < 2; hf++) {
          if (lane < 28) { sts128(stg + lane * 16, v[2 * hf]); sts128(stg + 448 + lane * 16, v[2 * hf + 1]); }
          __syncwarp();
          uint32_t m[8];
          ldsm4(m, stg + lx * 112 + (lane >> 3) * 16);
          ldsm4(m + 4, stg + lx * 112 + min(4 + (lane >> 3), 6) * 16);
#pragma unroll
          for (int t = 0; t < 7; t++) xr[2 * t + hf] = m[t];
          __syncwarp();
        }
      }
      float acc[28];
      mbar_wait(BAR(B_WO));
#pragma unroll 1
      for (int c = 0; c < 7; c++) {
        mbar_wait(BAR(B_A3 + c), 1);
        wg_fence();
#pragma unroll
        for (int ks = 0; ks < 4; ks++) wg_ss56<1>(acc, (uint64_t)(c * (PG / 16) + ((SMEM0 + 8 * PG + ks * 2048) >> 4) + (64u << 16)) | (uint64_t)8 << 32, desc(((c < 4 ? 2 * c : 2 * c + 12) + a) * (PG / 16), ks * 2048, 0), (c | ks) != 0);
      }
      wg_commit();
      mbar_wait(BAR(B_MOD2));
      wg_wait<0>(); keep<28>(acc);
      e_arrive_dep(BAR(B_S3MMA), hfma2(xr[1], xr[1], hmul2(xr[9], xr[9]))); e_arrive_remote(mapa(BAR(B_S3MMA2), peer));
#pragma unroll
      for (int t = 0; t < 7; t++) {
        const uint32_t ga = lds32(sb + OFF_GA + a * 112 + j * 4 + t * 16);
        xr[2 * t] = hfma2(ga, pack2(acc[4 * t], acc[4 * t + 1]), xr[2 * t]);
        xr[2 * t + 1] = hfma2(ga, pack2(acc[4 * t + 2], acc[4 * t + 3]), xr[2 * t + 1]);
      }
      store_cm<7>(xr, g_x1 + (h3 * 56 + 14 * c4 + 7 * a) * 512 + cmo);
      const uint32_t p0 = __byte_perm(__shfl_sync(~0u, xr[0], lane & 28), 0, 0x1010), p1 = __byte_perm(__shfl_sync(~0u, xr[1], lane & 28), 0, 0x1010);
      xr[14] = p0; xr[15] = p1;
      float s[4] = {}, q[4] = {};
#pragma unroll
      for (int i = 0; i < 4; i++) {
        uint32_t d[4], e[4];
#pragma unroll
        for (int k = 0; k < 4; k++) { d[k] = hsub2(xr[4 * i + k], (k & 1) ? p1 : p0); e[k] = hmul2(d[k], d[k]); }
        rowsum_mma(s, d);
        rowsum_mma(q, e);
      }
      if (j < 2) {
        const float sd = j ? s[2] : s[0];
        g_st1[(h3 * 8 + 2 * c4 + a) * 64 + r0 + 8 * j] = make_float2(fmaf(bf_lo(j ? p1 : p0), 56.f, sd), fmaf(-sd * (1.f / 56.f), sd, j ? q[2] : q[0]));
      }
      bar_sync(1, 256);
      if (warp == 0) e_release(C_X + h3);
    }
    uint32_t zp[28];
    {
      uint32_t A[28][4];
      mbar_wait(BAR(B_MOD2));
      uint32_t rh[2], rl[2], mr[2];
      mbar_wait(BAR(B_A4 + 7 * a));
#pragma unroll
      for (int e = 0; e < 2; e++) {
        float2 q[8];
        float mean = 0.f, m2 = 0.f;
#pragma unroll
        for (int i = 0; i < 8; i++) { q[i] = lds64f(sb + (a ? OFF_RAW1B : OFF_MW) + (r0 + 8 * e) * 8 + i * 512); mean += q[i].x; m2 += q[i].y; }
        mean *= 1.f / 448.f;
#pragma unroll
        for (int i = 0; i < 8; i++) { const float d = fmaf(q[i].x, 1.f / 56.f, -mean); m2 = fmaf(56.f * d, d, m2); }
        const float rstd = rsqrtf(fmaxf(m2, 0.f) * (1.f / 448.f) + 1e-5f);
        rh[e] = pack2(rstd, rstd);
        const float lo = rstd - bf_lo(rh[e]), nm = -mean * rstd;
        rl[e] = pack2(lo, lo); mr[e] = pack2(nm, nm);
      }
      if (a == 1) bar_arrive(4, 256);
      uint32_t chk = rh[0] | rh[1];
#pragma unroll
      for (int c = 0; c < 7; c++) {
        if (c) mbar_wait(BAR(B_A4 + 7 * a + c));
#pragma unroll
        for (int ks = 0; ks < 4; ks++) ldsm4(A[4 * c + ks], ldc + 7 * a * PG + c * PG + ks * 2048);
#pragma unroll
        for (int ks = 0; ks < 4; ks++) chk = hfma2(A[4 * c + ks][0], A[4 * c + ks][0], chk);
        if (c == 6) e_arrive_dep(BAR(B_A4RD + a), chk);
        if (c == 1 && a == 0) e_arrive_dep(BAR(B_A4E), chk);
#pragma unroll
        for (int h = 0; h < 2; h++) {
          uint4 cv = lds128(sb + OFF_MOD2 + j * 16 + (2 * c + h) * 64), sv = lds128(sb + OFF_MOD2 + 896 + j * 16 + (2 * c + h) * 64);
          uint32_t cw[4] = {cv.x, cv.y, cv.z, cv.w}, sw[4] = {sv.x, sv.y, sv.z, sv.w};
#pragma unroll
          for (int i = 0; i < 8; i++) {
            uint32_t& x = A[4 * c + 2 * h + (i >> 2)][i & 3];
            x = hfma2(hfma2(x, rh[i & 1], hfma2(x, rl[i & 1], mr[i & 1])), cw[i >> 1], sw[i >> 1]);
          }
        }
      }
#pragma unroll 1
      for (int p = 0; p < 2; p++) {
        float acc[56];
        mbar_wait(BAR(B_Z2W + 3 * p));
        bar_sync(4 + a, 256);
#pragma unroll
        for (int c = 0; c < 7; c++) {
          if (c == 2 || c == 4) { if (p) mbar_wait(BAR(B_Z1W + c / 2)); }
          if (c == 3 || c == 6) { if (!p) mbar_wait(BAR(B_Z2W + c / 3)); }
          wg_fence();
          const int q2 = c < 2 ? 16 + 2 * c : c == 2 ? 15 : c < 6 ? 14 + 2 * c : 0, l2 = c == 2 ? 11 : 1;
          const int q1 = c == 0 ? 4 : c == 1 ? 6 : c == 2 ? 9 : c == 3 ? 11 : c == 4 ? 16 : c == 5 ? 18 : 0, l1 = c == 1 ? 8 : 1;
          const uint32_t d16 = p ? (q1 * (PG / 16)) | (l1 * (PG / 16)) << 16 : (q2 * (PG / 16)) | (l2 * (PG / 16)) << 16;
#pragma unroll
          for (int ks = 0; ks < 4; ks++) wg_rs112<1>(acc, A[4 * c + ks], desc(d16, ks * 2048, 0), (c | ks) != 0);
          wg_commit();
          if (c == 3) { wg_wait<2>(); e_arrive(BAR(B_Z2C + p)); }
          if (c == 5) { wg_wait<2>(); if (p) e_arrive(BAR(B_Z1C + 1)); }
        }
        if (p == 0 || a == 0) bar_arrive(5 - a, 256);
        wg_wait<1>();
        if (p) e_arrive(BAR(B_Z1C + 2));
        wg_wait<0>(); keep<56>(acc);
        if (!p) e_arrive(BAR(B_Z2PASS));
        float s2[2] = {0.f, 0.f}, q2[2] = {0.f, 0.f};
#pragma unroll
        for (int i = 0; i < 28; i++) {
          const float x = gelu_h(acc[2 * i]), y = gelu_h(acc[2 * i + 1]);
          zp[i] = pack2(x, y);
          s2[i & 1] += x + y;
          q2[i & 1] = fmaf(x, x, fmaf(y, y, q2[i & 1]));
        }
        if (p == 0) {
          const uint32_t sp = PAGE(a ? 7 : 2), stg = sp + (lhi * 8 + lx) * 128 + (((2 * w + ((lane >> 3) & 1)) ^ lx) << 4);
#pragma unroll
          for (int t = 0; t < 7; t++) stsm4t(stg + t * 2048, zp[4 * t], zp[4 * t + 1], zp[4 * t + 2], zp[4 * t + 3]);
          float sv = (j & 1) ? s2[1] : s2[0], qv = (j & 1) ? q2[1] : q2[0];
          sv += __shfl_xor_sync(~0u, (j & 1) ? s2[0] : s2[1], 1); qv += __shfl_xor_sync(~0u, (j & 1) ? q2[0] : q2[1], 1);
          sv += __shfl_xor_sync(~0u, sv, 2); qv += __shfl_xor_sync(~0u, qv, 2);
          if (j < 2) {
            asm volatile("red.relaxed.gpu.global.add.v2.f32 [%0], {%1, %2};" ::"l"(g_st2 + st2pos(2 * rb + a) + r0 + 8 * j), "f"(sv), "f"(qv) : "memory");
            *(uint16_t*)(g_s.zs + (2 * rb + a) * 1024 + c8 * 128 + (((2 * w + j) ^ c8) << 4) + g * 2) = (uint16_t)pack2(sv * (1.f / 896.f), 0.f);
          }
          bar_sync(2 + a, 128);
          uint8_t* zg = g_z2t + ((size_t)(2 * rb + a) * FH + 112 * c8) * 128 + (tid & 127) * 16;
#pragma unroll
          for (int t = 0; t < 7; t++) stg128(zg + t * 2048, lds128(sp + (tid & 127) * 16 + t * 2048));
          bar_arrive(12 + a, 160);
        }
      }
    }
    {
      float acc[116];
      uint32_t A[2][16];
      const size_t row = 128 * rb + 64 * a + r0;
      uint16_t bs0, bs1;
      asm volatile("ld.global.nc.u16 %0, [%2];\nld.global.nc.u16 %1, [%2+16];" : "=h"(bs0), "=h"(bs1) : "l"(P.pbsp + row));
      auto prep = [&](int i, uint32_t* Af) {
        if ((i & 7) == 0) {
          mbar_wait(BAR(B_ST2 + (i >> 3)));
          if (i) {
            e_arrive_remote(mapa(BAR(B_X5FREE), peer));
          }
        }
        const int s = i & 3;
        mbar_wait(BAR(B_S5F + s), (i >> 2) & 1);
        const uint32_t pa = PG * (s == 0 ? 20 : 6 * s - 4) + a * PG;
#pragma unroll
        for (int ks = 0; ks < 4; ks++) ldsm4(Af + 4 * ks, lda[ks] + pa);
#pragma unroll
        for (int h = 0; h < 2; h++) {
          uint4 rv = lds128(sb + OFF_R5 + i * 128 + j * 32 + h * 16);
          uint32_t* p = Af + 8 * h;
          p[0] = hmul2(p[0], rv.x); p[1] = hmul2(p[1], rv.x); p[2] = hmul2(p[2], rv.y); p[3] = hmul2(p[3], rv.y);
          p[4] = hmul2(p[4], rv.z); p[5] = hmul2(p[5], rv.z); p[6] = hmul2(p[6], rv.w); p[7] = hmul2(p[7], rv.w);
        }
      };
      auto mma = [&](int i, const uint32_t* Af) {
        const int s = i & 3;
        wg_fence();
#pragma unroll
        for (int ks = 0; ks < 4; ks++) wg_rs232<0>(acc, Af + 4 * ks, desc((s == 0 ? 22 : 6 * s - 2) * (PG / 16), ks * 32, 16), (i | ks) != 0);
        wg_commit();
        wg_wait<1>();
        if (i > 0) e_arrive(BAR(i < 14 ? B_S5E + ((i - 1) & 3) : B_KPASS - 14 + i));
      };
#pragma unroll 1
      for (int i = 0; i < 16; i += 2) {
        if (i > 0) mma(i - 1, A[1]);
        prep(i, A[0]);
        mma(i, A[0]);
        prep(i + 1, A[1]);
      }
      mma(15, A[1]);
      mbar_wait(BAR(B_X5FREE));
      wg_wait<0>(); keep<116>(acc);
      float c0 = quad_sum(acc[112] + acc[113]), c1 = quad_sum(acc[114] + acc[115]);
      e_arrive(BAR(B_QPASS));
      const uint32_t xw = (a ? OFF_XB5_1 : OFF_XB5_0) + w * 3584, xoff = xw + lane * 16;
      const uint32_t rx = mapa(sb + xoff, peer), rbar = mapa(BAR(B_XB5 + a), peer);
#pragma unroll
      for (int q = 0; q < 7; q++) {
        const float* s = acc + 56 + 8 * q;
        st_async4(rx + q * 512, pack2(s[0] - c0, s[1] - c0), pack2(s[2] - c1, s[3] - c1), pack2(s[4] - c0, s[5] - c0), pack2(s[6] - c1, s[7] - c1), rbar);
      }
      c0 = bf_lo(bs0) - c0; c1 = bf_lo(bs1) - c1;
      mbar_wait(BAR(B_XB5 + a));
#pragma unroll
      for (int q = 0; q < 7; q++) {
        const uint4 v = lds128(sb + xoff + q * 512);
        const uint32_t vw[4] = {v.x, v.y, v.z, v.w};
#pragma unroll
        for (int e = 0; e < 4; e++) {
          const int i = 4 * q + e;
          const float cc = (e & 1) ? c1 : c0;
          zp[i] = hmul2(pack2(acc[2 * i] + cc + bf_lo(vw[e]), acc[2 * i + 1] + cc + bf_hi(vw[e])), zp[i]);
        }
      }
      store_cm<14>(zp, g_u + ((2 * rb + a) * 112 + 14 * c8) * 512 + cmo);
      uint32_t chk = 0;
#pragma unroll
      for (int q = 0; q < 7; q++) chk = hfma2(zp[4 * q], zp[4 * q], chk);
      e_arrive_dep(mapa(BAR(B_X6FREE), peer), chk);
      if (a == 1) e_arrive_dep(BAR(B_XRD), chk);
      bar_sync(1, 256);
      if (warp == 0) e_release(C_U + rb * 2 + kh);
    }
    {
      uint32_t xr[14];
#pragma unroll
      for (int t = 0; t < 14; t++) xr[t] = __ldcg((const uint32_t*)(g_x1 + ((2 * rb + a) * 56 + 7 * c8 + (t >> 1)) * 512 + (t & 1) * 64 + cmo));
      float acc[56];
      uint32_t A[2][28];
      auto mma6 = [&](int q, const uint32_t* Af) {
        wg_fence();
#pragma unroll
        for (int ks = 0; ks < 7; ks++) wg_rs112<1>(acc, Af + 4 * ks, desc(0, 2 * PG + q * 28672 + ks * 2048, 14336), (q | ks) != 0);
        wg_commit();
      };
      mbar_wait(BAR(B_B6));
      mma6(0, zp);
      mbar_wait(BAR(B_B6 + 1));
#pragma unroll
      for (int q = 1; q < 4; q++) {
        mbar_wait(BAR(B_A4 + 7 * a + q), 1);
        if (q == 3) wg_wait<1>();
#pragma unroll
        for (int ks = 0; ks < 7; ks++) ldsm4(A[q & 1] + 4 * ks, ldc + 16 * PG + (3 * a + q - 1) * 14336 + ks * 2048);
        mma6(q, A[q & 1]);
      }
      mbar_wait(BAR(B_X6FREE));
      wg_wait<0>(); keep<56>(acc);
      uint32_t ps[14];
#pragma unroll
      for (int i = 0; i < 14; i++) {
        ps[i] = pack2(kh ? acc[2 * i] : acc[28 + 2 * i], kh ? acc[2 * i + 1] : acc[29 + 2 * i]);
        acc[2 * i] = kh ? acc[28 + 2 * i] : acc[2 * i]; acc[2 * i + 1] = kh ? acc[29 + 2 * i] : acc[2 * i + 1];
      }
      const uint32_t xw = a * PG + w * 2048, xoff = xw + lane * 16;
      const uint32_t rx = mapa(sb + xoff, peer), rbar = mapa(BAR(B_XB6 + a), peer);
#pragma unroll
      for (int q = 0; q < 3; q++) st_async4(rx + q * 512, ps[4 * q], ps[4 * q + 1], ps[4 * q + 2], ps[4 * q + 3], rbar);
      st_async2(rx + 1536 - lane * 8, ps[12], ps[13], rbar);
      mbar_wait(BAR(B_XB6 + a));
#pragma unroll
      for (int q = 0; q < 3; q++) { uint4 v = lds128(sb + xoff + q * 512); ps[4 * q] = v.x; ps[4 * q + 1] = v.y; ps[4 * q + 2] = v.z; ps[4 * q + 3] = v.w; }
      { float2 v = lds64f(sb + xw + 1536 + lane * 8); ps[12] = __float_as_uint(v.x); ps[13] = __float_as_uint(v.y); }
#pragma unroll
      for (int t = 0; t < 7; t++) {
        const uint32_t gb = lds32(sb + OFF_GB + j * 4 + t * 16);
#pragma unroll
        for (int e = 0; e < 2; e++) {
          const int i = 2 * t + e;
          xr[i] = pack2(fmaf(bf_lo(gb), acc[2 * i] + bf_lo(ps[i]), bf_lo(xr[i])), fmaf(bf_hi(gb), acc[2 * i + 1] + bf_hi(ps[i]), bf_hi(xr[i])));
        }
      }
      __syncwarp();
      store_rows<7>(xr, sb + xw, P.out + (size_t)(128 * rb + 64 * a + 16 * w) * DM + 56 * c8, DM, lane);
    }
    if (b == 0 && tid == 0) st_relaxed(&g_epoch, ld_relaxed(&g_epoch) + 1);
  }
}

typedef CUresult (*EncodeFn)(CUtensorMap*, CUtensorMapDataType, cuuint32_t, void*, const cuuint64_t*, const cuuint64_t*, const cuuint32_t*,
                             const cuuint32_t*, CUtensorMapInterleave, CUtensorMapSwizzle, CUtensorMapL2promotion, CUtensorMapFloatOOBfill);

void make_map(EncodeFn enc, CUtensorMap* m, const void* ptr, uint64_t inner, uint64_t outer, uint32_t bi, uint32_t bo,
              CUtensorMapSwizzle sw = CU_TENSOR_MAP_SWIZZLE_128B) {
  cuuint64_t dims[2] = {inner, outer}, strides[1] = {inner * 2};
  cuuint32_t box[2] = {bi, bo}, es[2] = {1, 1};
  enc(m, CU_TENSOR_MAP_DATA_TYPE_BFLOAT16, 2, const_cast<void*>(ptr), dims, strides, box, es, CU_TENSOR_MAP_INTERLEAVE_NONE,
      sw, CU_TENSOR_MAP_L2_PROMOTION_L2_256B, CU_TENSOR_MAP_FLOAT_OOB_FILL_NONE);
}

}

extern "C" void kernel_launch(void* const* d_in, const int* in_sizes, int n_in, void* d_out, int out_size) {
  static EncodeFn enc = nullptr;
  if (!enc) {
    void* fn = nullptr;
    cudaDriverEntryPointQueryResult st;
    cudaGetDriverEntryPoint("cuTensorMapEncodeTiled", &fn, cudaEnableDefault, &st);
    enc = (EncodeFn)fn;
    cudaFuncSetAttribute(fused_kernel, cudaFuncAttributeMaxDynamicSharedMemorySize, SMEM_BYTES);
  }
  typedef const __nv_bfloat16* bp;
  Params P;
  P.px = (bp)d_in[0]; P.pwqkv = (bp)d_in[1]; P.pwo = (bp)d_in[2]; P.pwin = (bp)d_in[4]; P.pwsp = (bp)d_in[5]; P.pbsp = (bp)d_in[6];
  P.pwout = (bp)d_in[7]; P.pc = (bp)d_in[8]; P.pwmod = (bp)d_in[9]; P.out = (__nv_bfloat16*)d_out;
  make_map(enc, &P.wmod, d_in[9], 6 * DM, DM, 8, 224, CU_TENSOR_MAP_SWIZZLE_NONE);
  make_map(enc, &P.wmods, d_in[9], 6 * DM, DM, 224, 224, CU_TENSOR_MAP_SWIZZLE_NONE);
  make_map(enc, &P.x, d_in[0], DM, SEQ, 64, 128);
  make_map(enc, &P.wqkv, d_in[1], 3 * DM, DM, 64, 64);
  make_map(enc, &P.wo64, d_in[2], DM, DM, 56, 64);
  make_map(enc, &P.wo48, d_in[2], DM, DM, 56, 64);
  make_map(enc, &P.win64, d_in[4], 2 * FH, DM, 64, 64);
  make_map(enc, &P.win48, d_in[4], 2 * FH, DM, 48, 64);
  make_map(enc, &P.wsp, d_in[5], SEQ, SEQ, 64, 128);
  make_map(enc, &P.wout64, d_in[7], DM, FH, 64, 112);
  make_map(enc, &P.wout48, d_in[7], DM, FH, 48, 112);
  fused_kernel<<<132, 384, SMEM_BYTES, cudaStreamPerThread>>>(P);
}
```
